```python
import torch

def _softmax(x, axis=-1):
    return torch.softmax(x, dim=axis)
def _gelu(x):
    return torch.nn.functional.gelu(x, approximate="tanh")
def _silu(x):
    return torch.nn.functional.silu(x)
def _sigmoid(x):
    return torch.sigmoid(x)
def _layernorm(x, axis=-1, eps=1e-5):
    m = x.mean(dim=axis, keepdim=True)
    v = x.var(dim=axis, keepdim=True, unbiased=False)
    return (x - m) / torch.sqrt(v + eps)
def _scatter_add(tgt, idx, src, axis=0):
    return tgt.clone().index_add_(axis, idx, src)
def _segment_sum(src, seg, n):
    out = torch.zeros((n,) + src.shape[1:], dtype=src.dtype)
    return out.index_add_(0, seg, src)
def _pad(x, pw):
    flat = tuple(v for pair in reversed(pw) for v in pair)
    return torch.nn.functional.pad(x, flat)

kernel_name = 'interleave_layers__linear_attn_block__swiglu_ffn__prompt'

def setup_inputs():

    _w = (lambda a: (lambda t: t.to(torch.bfloat16) if t.is_floating_point() else t)(torch.as_tensor(a)))
    def _A_setup():
        B, S, D = 1, 2048, 1024
        return {
            "x": _w((lambda *s: torch.randn(*s, dtype=torch.bfloat16) * 0.05)(B, S, D)),
            "wqkv": _w((lambda *s: torch.randn(*s, dtype=torch.bfloat16) * 0.05)(D, 3 * D)),
            "wo": _w((lambda *s: torch.randn(*s, dtype=torch.bfloat16) * 0.05)(D, D)),
        }
    _A_in = _A_setup()

    def _B_setup():
        B, S, D, F = 1, 2048, 1024, 3584
        return {
            "x": _w((lambda *s: torch.randn(*s, dtype=torch.bfloat16) * 0.05)(B, S, D)),
            "w_gate": _w((lambda *s: torch.randn(*s, dtype=torch.bfloat16) * 0.05)(D, F)),
            "w_up": _w((lambda *s: torch.randn(*s, dtype=torch.bfloat16) * 0.05)(D, F)),
            "w_down": _w((lambda *s: torch.randn(*s, dtype=torch.bfloat16) * 0.05)(F, D)),
        }
    _B_in = _B_setup()

    return {
        "A_x": _A_in["x"],
        "A_wqkv": _A_in["wqkv"],
        "A_wo": _A_in["wo"],
        "B_x": _B_in["x"],
        "B_w_gate": _B_in["w_gate"],
        "B_w_up": _B_in["w_up"],
        "B_w_down": _B_in["w_down"],
    }

def reference(A_x, A_wqkv, A_wo, B_x, B_w_gate, B_w_up, B_w_down):
    def _A_ref(x, wqkv, wo):
        B, S, D = x.shape
        H = 32; Dh = D // H
        qkv = (lambda x, *d: x.permute(*d))((x @ wqkv).reshape(B, S, 3, H, Dh), 2, 0, 3, 1, 4)
        q, k, v = qkv[0], qkv[1], qkv[2]
        phi = lambda t: torch.where(t > 0, t + 1, torch.exp(t)) + 1e-6
        pq, pk = phi(q), phi(k)
        kv = torch.einsum("bhsd,bhse->bhde", pk, v)
        z = torch.einsum("bhsd->bhd", pk)
        num = torch.einsum("bhqd,bhde->bhqe", pq, kv)
        den = torch.einsum("bhqd,bhd->bhq", pq, z)[..., None] + 1e-6
        o = num / den
        return (lambda x, *d: x.permute(*d))(o, 0, 2, 1, 3).reshape(B, S, D) @ wo

    def _B_ref(x, w_gate, w_up, w_down):
        g = _silu(x @ w_gate)
        u = x @ w_up
        return (g * u) @ w_down

    x = A_x
    x = x + _A_ref(_layernorm(x, axis=-1), A_wqkv, A_wo)
    x = x + _B_ref(_layernorm(x, axis=-1), B_w_gate, B_w_up, B_w_down)
    x = x + _A_ref(_layernorm(x, axis=-1), A_wqkv, A_wo)
    x = x + _B_ref(_layernorm(x, axis=-1), B_w_gate, B_w_up, B_w_down)
    return x
```

```cpp
#include <cuda_runtime.h>
#include <cuda_bf16.h>
#include <cuda.h>
#include <stdint.h>

#define TIMING 0

namespace {

constexpr int SEQ = 2048, DM = 1024, FF = 3584;
constexpr int STAGES = 5;
constexpr int STAGE_BYTES = 32768;
constexpr int NT = 12;
constexpr int KS_LAYER = 11 * 16 + 56;

constexpr int SM_S = STAGES * STAGE_BYTES;
constexpr int SM_ONES = SM_S + 32768;
constexpr int SM_KV = SM_ONES + 2048;
constexpr int SM_CS = SM_KV + 10240;
constexpr int SM_RS = SM_CS + 5760;
constexpr int SM_BAR = SM_RS + 2048;
constexpr int SM_TOTAL = SM_BAR + 256 + 1024;

constexpr int C_O = 0, C_X1 = 2, C_X1S = 4, C_H = 5, C_X2 = 12, C_X2S = 14;
constexpr int CNT_STRIDE = 32;

struct Params {
  CUtensorMap x0, x1, x2, out, o, h, wqkv, wo, wg, wu, wd;
  const __nv_bfloat16* x0p;
};

__device__ __nv_bfloat16 g_x1[SEQ * DM];
__device__ __nv_bfloat16 g_x2[SEQ * DM];
__device__ __nv_bfloat16 g_o[SEQ * DM];
__device__ __nv_bfloat16 g_h[SEQ * FF];
__device__ float2 g_stats[4][SEQ][8];
__device__ float g_cs[10240];
__device__ float g_kv[2][32][1056];
__device__ unsigned g_cnt[2 * 16 * 16 * CNT_STRIDE];
__device__ unsigned g_kvcnt[2 * 8 * CNT_STRIDE];

__device__ __forceinline__ void wgmma_n128(float (&d)[64], uint64_t da, uint64_t db, int scale_d) {
  asm volatile("{\n.reg .pred p;\nsetp.ne.b32 p, %66, 0;\n"
    "wgmma.mma_async.sync.aligned.m64n128k16.f32.bf16.bf16 {%0, %1, %2, %3, %4, %5, %6, %7, %8, %9, %10, %11, %12, %13, %14, %15, %16, %17, %18, %19, %20, %21, %22, %23, %24, %25, %26, %27, %28, %29, %30, %31, %32, %33, %34, %35, %36, %37, %38, %39, %40, %41, %42, %43, %44, %45, %46, %47, %48, %49, %50, %51, %52, %53, %54, %55, %56, %57, %58, %59, %60, %61, %62, %63}, %64, %65, p, 1, 1, 0, 1;\n}\n"
    : "+f"(d[0]), "+f"(d[1]), "+f"(d[2]), "+f"(d[3]), "+f"(d[4]), "+f"(d[5]), "+f"(d[6]), "+f"(d[7]), "+f"(d[8]), "+f"(d[9]), "+f"(d[10]), "+f"(d[11]), "+f"(d[12]), "+f"(d[13]), "+f"(d[14]), "+f"(d[15]), "+f"(d[16]), "+f"(d[17]), "+f"(d[18]), "+f"(d[19]), "+f"(d[20]), "+f"(d[21]), "+f"(d[22]), "+f"(d[23]), "+f"(d[24]), "+f"(d[25]), "+f"(d[26]), "+f"(d[27]), "+f"(d[28]), "+f"(d[29]), "+f"(d[30]), "+f"(d[31]), "+f"(d[32]), "+f"(d[33]), "+f"(d[34]), "+f"(d[35]), "+f"(d[36]), "+f"(d[37]), "+f"(d[38]), "+f"(d[39]), "+f"(d[40]), "+f"(d[41]), "+f"(d[42]), "+f"(d[43]), "+f"(d[44]), "+f"(d[45]), "+f"(d[46]), "+f"(d[47]), "+f"(d[48]), "+f"(d[49]), "+f"(d[50]), "+f"(d[51]), "+f"(d[52]), "+f"(d[53]), "+f"(d[54]), "+f"(d[55]), "+f"(d[56]), "+f"(d[57]), "+f"(d[58]), "+f"(d[59]), "+f"(d[60]), "+f"(d[61]), "+f"(d[62]), "+f"(d[63])
    : "l"(da), "l"(db), "r"(scale_d));
}

__device__ __forceinline__ void wgmma_n72_tt(float (&d)[36], uint64_t da, uint64_t db, int scale_d) {
  asm volatile("{\n.reg .pred p;\nsetp.ne.b32 p, %38, 0;\n"
    "wgmma.mma_async.sync.aligned.m64n72k16.f32.bf16.bf16 {%0, %1, %2, %3, %4, %5, %6, %7, %8, %9, %10, %11, %12, %13, %14, %15, %16, %17, %18, %19, %20, %21, %22, %23, %24, %25, %26, %27, %28, %29, %30, %31, %32, %33, %34, %35}, %36, %37, p, 1, 1, 1, 1;\n}\n"
    : "+f"(d[0]), "+f"(d[1]), "+f"(d[2]), "+f"(d[3]), "+f"(d[4]), "+f"(d[5]), "+f"(d[6]), "+f"(d[7]), "+f"(d[8]), "+f"(d[9]), "+f"(d[10]), "+f"(d[11]), "+f"(d[12]), "+f"(d[13]), "+f"(d[14]), "+f"(d[15]), "+f"(d[16]), "+f"(d[17]), "+f"(d[18]), "+f"(d[19]), "+f"(d[20]), "+f"(d[21]), "+f"(d[22]), "+f"(d[23]), "+f"(d[24]), "+f"(d[25]), "+f"(d[26]), "+f"(d[27]), "+f"(d[28]), "+f"(d[29]), "+f"(d[30]), "+f"(d[31]), "+f"(d[32]), "+f"(d[33]), "+f"(d[34]), "+f"(d[35])
    : "l"(da), "l"(db), "r"(scale_d));
}

__device__ __forceinline__ uint32_t smem_u32(const void* p) { return (uint32_t)__cvta_generic_to_shared(p); }
__device__ __forceinline__ void mbar_init(uint32_t bar, uint32_t count) { asm volatile("mbarrier.init.shared::cta.b64 [%0], %1;" :: "r"(bar), "r"(count)); }
__device__ __forceinline__ void mbar_expect_tx(uint32_t bar, uint32_t bytes) { asm volatile("mbarrier.arrive.expect_tx.shared::cta.b64 _, [%0], %1;" :: "r"(bar), "r"(bytes) : "memory"); }
__device__ __forceinline__ void mbar_arrive(uint32_t bar) { asm volatile("mbarrier.arrive.shared::cta.b64 _, [%0];" :: "r"(bar) : "memory"); }
__device__ __forceinline__ void mbar_arrive_cluster(uint32_t bar, uint32_t cta) {
  asm volatile("{\n.reg .b32 ra;\nmapa.shared::cluster.u32 ra, %0, %1;\nmbarrier.arrive.shared::cluster.b64 _, [ra];\n}\n" :: "r"(bar), "r"(cta) : "memory");
}
__device__ __forceinline__ bool mbar_try_wait(uint32_t bar, uint32_t parity) {
  uint32_t ok;
  asm volatile("{\n.reg .pred p;\nmbarrier.try_wait.parity.shared::cta.b64 p, [%1], %2;\nselp.u32 %0, 1, 0, p;\n}\n" : "=r"(ok) : "r"(bar), "r"(parity) : "memory");
  return ok;
}
__device__ __forceinline__ void mbar_wait(uint32_t bar, uint32_t parity) {
  if (mbar_try_wait(bar, parity)) return;
  int it = 0;
  while (!mbar_try_wait(bar, parity)) { if (++it > (1 << 21)) __trap(); }
}
__device__ __forceinline__ unsigned ld_acquire(const unsigned* p) { unsigned v; asm volatile("ld.acquire.gpu.global.u32 %0, [%1];" : "=r"(v) : "l"(p) : "memory"); return v; }
__device__ __forceinline__ void red_release(unsigned* p) { asm volatile("red.release.gpu.global.add.u32 [%0], 1;" :: "l"(p) : "memory"); }
__device__ __forceinline__ void flag_wait(const unsigned* p, unsigned target) {
  int it = 0;
  while ((int)(ld_acquire(p) - target) < 0) { if (++it > (1 << 22)) __trap(); }
}
__device__ __forceinline__ void tma_load_2d(uint32_t dst, const CUtensorMap* tm, int c0, int c1, uint32_t bar) {
  asm volatile("cp.async.bulk.tensor.2d.shared::cluster.global.mbarrier::complete_tx::bytes [%0], [%1, {%3, %4}], [%2];"
    :: "r"(dst), "l"(tm), "r"(bar), "r"(c0), "r"(c1) : "memory");
}
__device__ __forceinline__ void tma_load_2d_mc(uint32_t dst, const CUtensorMap* tm, int c0, int c1, uint32_t bar, uint16_t mask) {
  asm volatile("cp.async.bulk.tensor.2d.shared::cluster.global.mbarrier::complete_tx::bytes.multicast::cluster [%0], [%1, {%3, %4}], [%2], %5;"
    :: "r"(dst), "l"(tm), "r"(bar), "r"(c0), "r"(c1), "h"(mask) : "memory");
}
__device__ __forceinline__ void tma_store_2d(const CUtensorMap* tm, uint32_t src, int c0, int c1) {
  asm volatile("cp.async.bulk.tensor.2d.global.shared::cta.bulk_group [%0, {%2, %3}], [%1];" :: "l"(tm), "r"(src), "r"(c0), "r"(c1) : "memory");
}
__device__ __forceinline__ void bulk_commit() { asm volatile("cp.async.bulk.commit_group;" ::: "memory"); }
template <int N> __device__ __forceinline__ void bulk_wait() { asm volatile("cp.async.bulk.wait_group %0;" :: "n"(N) : "memory"); }
__device__ __forceinline__ void fence_async_smem() { asm volatile("fence.proxy.async.shared::cta;" ::: "memory"); }
__device__ __forceinline__ void fence_async_global() { asm volatile("fence.proxy.async.global;" ::: "memory"); }
__device__ __forceinline__ void wgmma_fence() { asm volatile("wgmma.fence.sync.aligned;" ::: "memory"); }
__device__ __forceinline__ void wgmma_commit() { asm volatile("wgmma.commit_group.sync.aligned;" ::: "memory"); }
template <int N> __device__ __forceinline__ void wgmma_wait() { asm volatile("wgmma.wait_group.sync.aligned %0;" :: "n"(N) : "memory"); }
__device__ __forceinline__ uint64_t make_desc(uint32_t addr, uint32_t lbo, uint32_t sbo) {
  return (uint64_t)((addr & 0x3FFFF) >> 4) | ((uint64_t)(lbo >> 4) << 16) | ((uint64_t)(sbo >> 4) << 32) | (1ull << 62);
}
__device__ __forceinline__ void cluster_sync() {
  asm volatile("barrier.cluster.arrive.release.aligned;\nbarrier.cluster.wait.acquire.aligned;" ::: "memory");
}
__device__ __forceinline__ uint32_t cluster_ctarank() { uint32_t r; asm volatile("mov.u32 %0, %%cluster_ctarank;" : "=r"(r)); return r; }
__device__ __forceinline__ void bar_sync(int id, int n) { asm volatile("bar.sync %0, %1;" :: "r"(id), "r"(n) : "memory"); }
__device__ __forceinline__ void bar_arrive(int id, int n) { asm volatile("bar.arrive %0, %1;" :: "r"(id), "r"(n) : "memory"); }
__device__ __forceinline__ void stmatrix_x4(uint32_t addr, uint32_t r0, uint32_t r1, uint32_t r2, uint32_t r3) {
  asm volatile("stmatrix.sync.aligned.m8n8.x4.shared.b16 [%0], {%1, %2, %3, %4};" :: "r"(addr), "r"(r0), "r"(r1), "r"(r2), "r"(r3) : "memory");
}
__device__ __forceinline__ void ldmatrix_x4_t(uint32_t addr, uint32_t (&r)[4]) {
  asm volatile("ldmatrix.sync.aligned.m8n8.x4.trans.shared.b16 {%0, %1, %2, %3}, [%4];" : "=r"(r[0]), "=r"(r[1]), "=r"(r[2]), "=r"(r[3]) : "r"(addr) : "memory");
}
__device__ __forceinline__ void mma_bf16(float (&d)[4], uint32_t a0, uint32_t a1, uint32_t a2, uint32_t a3, uint32_t b0, uint32_t b1) {
  asm("mma.sync.aligned.m16n8k16.row.col.f32.bf16.bf16.f32 {%0, %1, %2, %3}, {%4, %5, %6, %7}, {%8, %9}, {%0, %1, %2, %3};"
    : "+f"(d[0]), "+f"(d[1]), "+f"(d[2]), "+f"(d[3]) : "r"(a0), "r"(a1), "r"(a2), "r"(a3), "r"(b0), "r"(b1));
}
__device__ __forceinline__ uint32_t pack_bf16(float a, float b) { uint32_t r; asm("cvt.rn.bf16x2.f32 %0, %1, %2;" : "=r"(r) : "f"(b), "f"(a)); return r; }
__device__ __forceinline__ float bf_lo(uint32_t v) { return __uint_as_float(v << 16); }
__device__ __forceinline__ float bf_hi(uint32_t v) { return __uint_as_float(v & 0xffff0000u); }
__device__ __forceinline__ float ex2f(float x) { float r; asm("ex2.approx.ftz.f32 %0, %1;" : "=f"(r) : "f"(x)); return r; }
__device__ __forceinline__ float rcpf(float x) { float r; asm("rcp.approx.ftz.f32 %0, %1;" : "=f"(r) : "f"(x)); return r; }
__device__ __forceinline__ float4 lds128(uint32_t a) { float4 v; asm volatile("ld.shared.v4.f32 {%0, %1, %2, %3}, [%4];" : "=f"(v.x), "=f"(v.y), "=f"(v.z), "=f"(v.w) : "r"(a)); return v; }
__device__ __forceinline__ float2 lds64(uint32_t a) { float2 v; asm volatile("ld.shared.v2.f32 {%0, %1}, [%2];" : "=f"(v.x), "=f"(v.y) : "r"(a)); return v; }
__device__ __forceinline__ void red_add_v2(float* p, float a, float b) { asm volatile("red.relaxed.gpu.global.add.v2.f32 [%0], {%1, %2};" :: "l"(p), "f"(a), "f"(b) : "memory"); }
__device__ __forceinline__ void red_add(float* p, float a) { asm volatile("red.relaxed.gpu.global.add.f32 [%0], %1;" :: "l"(p), "f"(a) : "memory"); }

template <int N> __device__ __forceinline__ void pin_regs(float (&d)[N]) {
  #pragma unroll
  for (int i = 0; i < N; i++) asm volatile("" : "+f"(d[i]) :: "memory");
}

constexpr float LOG2E = 1.4426950408889634f;

__device__ __forceinline__ float phi(float y, float rs, float rsl) {
  float a = fmaf(y, rs, 1.000001f);
  float b = ex2f(y * rsl) + 1e-6f;
  return y > 0.f ? a : b;
}

__device__ __forceinline__ int kchunk(int T, int k) {
  if (T == 11) return 7 * (k & 7) + (k >> 3);
  return ((k & 7) << 1) | (k >> 3);
}

__global__ void __launch_bounds__(256) pre_kernel(const __nv_bfloat16* __restrict__ x, const __nv_bfloat16* __restrict__ wqkv,
                                                  const __nv_bfloat16* __restrict__ wg, const __nv_bfloat16* __restrict__ wu) {
  __shared__ float red[32][65];
  int b = blockIdx.x, tid = threadIdx.x;
  if (b < 160) {
    int col0 = b * 64;
    const __nv_bfloat16* w; int ld, c;
    if (col0 < 3072) { w = wqkv; ld = 3072; c = col0; }
    else if (col0 < 3072 + FF) { w = wg; ld = FF; c = col0 - 3072; }
    else { w = wu; ld = FF; c = col0 - 3072 - FF; }
    int cg = tid & 7, rg = tid >> 3;
    float s[8] = {0, 0, 0, 0, 0, 0, 0, 0};
    #pragma unroll 8
    for (int r = rg; r < DM; r += 32) {
      uint4 v = __ldg((const uint4*)(w + (size_t)r * ld + c + cg * 8));
      s[0] += bf_lo(v.x); s[1] += bf_hi(v.x); s[2] += bf_lo(v.y); s[3] += bf_hi(v.y);
      s[4] += bf_lo(v.z); s[5] += bf_hi(v.z); s[6] += bf_lo(v.w); s[7] += bf_hi(v.w);
    }
    for (int e = 0; e < 8; e++) red[rg][cg * 8 + e] = s[e];
    __syncthreads();
    if (tid < 64) { float t = 0; for (int r = 0; r < 32; r++) t += red[r][tid]; g_cs[col0 + tid] = t; }
  } else if (b < 160 + 256) {
    int row = (b - 160) * 8 + (tid >> 5), lane = tid & 31;
    const uint4* p = (const uint4*)(x + (size_t)row * DM + lane * 32);
    float v[32];
    #pragma unroll
    for (int i = 0; i < 4; i++) {
      uint4 u = __ldg(p + i);
      v[i * 8 + 0] = bf_lo(u.x); v[i * 8 + 1] = bf_hi(u.x); v[i * 8 + 2] = bf_lo(u.y); v[i * 8 + 3] = bf_hi(u.y);
      v[i * 8 + 4] = bf_lo(u.z); v[i * 8 + 5] = bf_hi(u.z); v[i * 8 + 6] = bf_lo(u.w); v[i * 8 + 7] = bf_hi(u.w);
    }
    float s = 0;
    #pragma unroll
    for (int i = 0; i < 32; i++) s += v[i];
    s += __shfl_xor_sync(~0u, s, 1); s += __shfl_xor_sync(~0u, s, 2);
    float m = s * (1.f / 128.f), q = 0;
    #pragma unroll
    for (int i = 0; i < 32; i++) { float d = v[i] - m; q = fmaf(d, d, q); }
    q += __shfl_xor_sync(~0u, q, 1); q += __shfl_xor_sync(~0u, q, 2);
    if ((lane & 3) == 0) g_stats[0][row][lane >> 2] = make_float2(s, q);
  } else {
    int n = (b - 416) * 256 + tid;
    for (int i = n; i < 2 * 32 * 1056; i += 64 * 256) (&g_kv[0][0][0])[i] = 0.f;
    for (int i = n; i < 2 * 16 * 16 * CNT_STRIDE; i += 64 * 256) g_cnt[i] = 0;
    for (int i = n; i < 2 * 8 * CNT_STRIDE; i += 64 * 256) g_kvcnt[i] = 0;
  }
}

__global__ void __cluster_dims__(2, 1, 1) __launch_bounds__(384, 1) mega_kernel(const __grid_constant__ Params P) {
  extern __shared__ uint8_t smem_raw[];
  const uint32_t sbase = (smem_u32(smem_raw) + 1023) & ~1023u;
  const uint32_t bar_full = sbase + SM_BAR, bar_empty = bar_full + 8 * STAGES;
  const uint32_t bar_rsA = bar_empty + 8 * STAGES, bar_rsB = bar_rsA + 8, bar_kv = bar_rsB + 8;
  const int warp = __shfl_sync(0xffffffff, threadIdx.x >> 5, 0), lane = threadIdx.x & 31;
  const uint32_t rank = cluster_ctarank();
  int mi, nj;
  { int p = blockIdx.x >> 1, g = p & 7, sl = p >> 3; mi = (g >> 1) * 4 + (sl >> 1); nj = ((g & 1) * 2 + (sl & 1)) * 2 + rank; }
  const int row0 = mi * 128;

  if (threadIdx.x == 0) {
    for (int s = 0; s < STAGES; s++) { mbar_init(bar_full + 8 * s, 2); mbar_init(bar_empty + 8 * s, 2); }
    mbar_init(bar_rsA, 2); mbar_init(bar_rsB, 2); mbar_init(bar_kv, 2);
    asm volatile("fence.mbarrier_init.release.cluster;" ::: "memory");
  }
  for (int i = threadIdx.x; i < 512; i += 384) asm volatile("st.shared.u32 [%0], %1;" :: "r"(sbase + SM_ONES + i * 4), "r"(0x3f803f80u) : "memory");
  for (int i = threadIdx.x; i < 1280; i += 384) {
    int tl = i >> 7, c = i & 127;
    int gc;
    if (tl < 2) gc = (c < 64 ? 1024 : 2048 - 64) + nj * 128 + tl * 64 + c;
    else if (tl == 2) gc = nj * 128 + c;
    else gc = 3072 + (c < 64 ? 0 : FF - 64) + nj * 448 + (tl - 3) * 64 + c;
    float v = g_cs[gc];
    int t = (c >> 1) & 3, blk = c >> 3;
    asm volatile("st.shared.f32 [%0], %1;" :: "r"(sbase + SM_CS + tl * 576 + t * 144 + (blk * 2 + (c & 1)) * 4), "f"(v) : "memory");
  }
  fence_async_smem();
  __syncthreads();
  cluster_sync();

  unsigned* cnt_base = g_cnt + mi * 16 * CNT_STRIDE;

  if (warp >= 8) {
    asm volatile("setmaxnreg.dec.sync.aligned.u32 40;");
    if (warp == 8) {
      if (lane == 0) {
        int s = 0; uint32_t ph = 1;
        for (int L = 0; L < 2; L++) {
          unsigned* cnt = cnt_base + L * 256 * CNT_STRIDE;
          for (int T = 0; T < NT; T++) {
            const CUtensorMap* tm = T < 3 ? (L == 0 ? &P.x0 : &P.x2) : T == 3 ? &P.o : T < 11 ? &P.x1 : &P.h;
            const int nk = T == 11 ? 56 : 16;
            const unsigned* dep = nullptr;
            if (T == 0 && L == 1) dep = cnt_base + C_X2 * CNT_STRIDE;
            else if (T == 3) dep = cnt + C_O * CNT_STRIDE;
            else if (T == 4) dep = cnt + C_X1 * CNT_STRIDE;
            else if (T == 11) dep = cnt + C_H * CNT_STRIDE;
            for (int k = 0; k < nk; k++) {
              if (dep && (k & 7) == 0) { flag_wait(dep + (k >> 3) * CNT_STRIDE, 8); fence_async_global(); }
              mbar_wait(bar_empty + 8 * s, ph);
              mbar_expect_tx(bar_full + 8 * s, 16384);
              tma_load_2d_mc(sbase + s * STAGE_BYTES + rank * 8192, tm, kchunk(T, k) * 64, row0 + rank * 64, bar_full + 8 * s, 3);
              if (++s == STAGES) { s = 0; ph ^= 1; }
            }
          }
        }
      }
    } else if (warp == 9) {
      if (lane == 0) {
        int s = 0; uint32_t ph = 1;
        for (int L = 0; L < 2; L++) {
          for (int T = 0; T < NT; T++) {
            const CUtensorMap *t0, *t1; int c0, c1;
            if (T < 2) { t0 = t1 = &P.wqkv; c0 = 1024 + nj * 128 + T * 64; c1 = c0 + 1024; }
            else if (T == 2) { t0 = t1 = &P.wqkv; c0 = nj * 128; c1 = c0 + 64; }
            else if (T == 3) { t0 = t1 = &P.wo; c0 = nj * 128; c1 = c0 + 64; }
            else if (T < 11) { t0 = &P.wg; t1 = &P.wu; c0 = c1 = nj * 448 + (T - 4) * 64; }
            else { t0 = t1 = &P.wd; c0 = nj * 128; c1 = c0 + 64; }
            const int nk = T == 11 ? 56 : 16;
            for (int k = 0; k < nk; k++) {
              mbar_wait(bar_empty + 8 * s, ph);
              mbar_expect_tx(bar_full + 8 * s, 16384);
              uint32_t sb = sbase + s * STAGE_BYTES + 16384;
              int kc = kchunk(T, k) * 64;
              tma_load_2d(sb, t0, c0, kc, bar_full + 8 * s);
              tma_load_2d(sb + 8192, t1, c1, kc, bar_full + 8 * s);
              if (++s == STAGES) { s = 0; ph ^= 1; }
            }
          }
        }
      }
    } else {
      const int aw = warp - 10;
      for (int L = 0; L < 2; L++) {
        for (int step = 0; step < 3; step++) {
          if (step == 1) {
            if (lane == 0) flag_wait(g_kvcnt + (L * 8 + nj) * CNT_STRIDE, 32);
            __syncwarp();
            #pragma unroll 1
            for (int hh = 0; hh < 2; hh++) {
              const float* src = g_kv[L][nj * 4 + aw * 2 + hh];
              uint32_t dst = sbase + SM_KV + (aw * 2 + hh) * 2560;
              float4 v[8];
              #pragma unroll
              for (int i = 0; i < 8; i++) v[i] = __ldcg((const float4*)src + i * 32 + lane);
              float z = __ldcg(src + 1024 + lane);
              #pragma unroll
              for (int i = 0; i < 8; i++) {
                int r = i * 4 + (lane >> 3);
                asm volatile("st.shared.v2.u32 [%0], {%1, %2};" :: "r"(dst + r * 80 + (lane & 7) * 8), "r"(pack_bf16(v[i].x, v[i].y)), "r"(pack_bf16(v[i].z, v[i].w)) : "memory");
              }
              uint32_t zz = pack_bf16(z, z);
              asm volatile("st.shared.v4.u32 [%0], {%1, %1, %1, %1};" :: "r"(dst + lane * 80 + 64), "r"(zz) : "memory");
            }
            __syncwarp();
            if (lane == 0) mbar_arrive(bar_kv);
          } else {
            const int sidx = L * 2 + (step >> 1);
            if (lane == 0) {
              if (step == 0) { if (L == 1) flag_wait(cnt_base + C_X2S * CNT_STRIDE, 8); }
              else flag_wait(cnt_base + (L * 256 + C_X1S) * CNT_STRIDE, 8);
            }
            __syncwarp();
            #pragma unroll 1
            for (int rr = 0; rr < 2; rr++) {
              int r = aw * 64 + rr * 32 + lane;
              const float4* sp = (const float4*)&g_stats[sidx][row0 + r][0];
              float4 a = __ldcg(sp), b = __ldcg(sp + 1), c = __ldcg(sp + 2), d = __ldcg(sp + 3);
              float mean = (a.x + a.z + b.x + b.z + c.x + c.z + d.x + d.z) * (1.f / 1024.f);
              float m2 = a.y + a.w + b.y + b.w + c.y + c.w + d.y + d.w;
              float e, q = 0;
              e = a.x * (1.f / 128.f) - mean; q = fmaf(e, e, q); e = a.z * (1.f / 128.f) - mean; q = fmaf(e, e, q);
              e = b.x * (1.f / 128.f) - mean; q = fmaf(e, e, q); e = b.z * (1.f / 128.f) - mean; q = fmaf(e, e, q);
              e = c.x * (1.f / 128.f) - mean; q = fmaf(e, e, q); e = c.z * (1.f / 128.f) - mean; q = fmaf(e, e, q);
              e = d.x * (1.f / 128.f) - mean; q = fmaf(e, e, q); e = d.z * (1.f / 128.f) - mean; q = fmaf(e, e, q);
              float var = (m2 + 128.f * q) * (1.f / 1024.f);
              float rstd = rsqrtf(var + 1e-5f);
              asm volatile("st.shared.v2.f32 [%0], {%1, %2};" :: "r"(sbase + SM_RS + (step >> 1) * 1024 + r * 8), "f"(mean), "f"(rstd) : "memory");
            }
            __syncwarp();
            if (lane == 0) mbar_arrive(step == 0 ? bar_rsA : bar_rsB);
          }
        }
      }
    }
    cluster_sync();
  } else {
    asm volatile("setmaxnreg.inc.sync.aligned.u32 232;");
    const int wg = warp >> 2, w = warp & 3, tid = threadIdx.x & 127;
    const int g = lane >> 2, t = lane & 3;
    const bool elect = tid == 0;
    float acc0[64], acc1[64];
    const int st_row = w * 16 + (lane & 7) + ((lane >> 3) & 1) * 8;
    const int st_ch = lane >> 4;
    const uint32_t myS = sbase + SM_S + wg * 16384;
    if (wg == 1) bar_arrive(1, 256);

    for (int L = 0; L < 2; L++) {
      unsigned* cnt = cnt_base + L * 256 * CNT_STRIDE;
      #pragma unroll 1
      for (int T = wg; T < NT; T += 2) {
        const bool resid = (T == 3 || T == 11);
        const int nk = T == 11 ? 56 : 16;
        if (resid) {
          const __nv_bfloat16* src = T == 11 ? g_x1 : (L == 0 ? P.x0p : g_x2);
          const uint32_t* p = (const uint32_t*)(src + (size_t)(row0 + w * 16 + g) * DM + nj * 128 + t * 2);
          #pragma unroll
          for (int b = 0; b < 16; b++) {
            uint32_t v0 = __ldcg(p + b * 4), v1 = __ldcg(p + b * 4 + 8 * (DM / 2));
            uint32_t v2 = __ldcg(p + b * 4 + 64 * (DM / 2)), v3 = __ldcg(p + b * 4 + 72 * (DM / 2));
            acc0[b * 4] = bf_lo(v0); acc0[b * 4 + 1] = bf_hi(v0); acc0[b * 4 + 2] = bf_lo(v1); acc0[b * 4 + 3] = bf_hi(v1);
            acc1[b * 4] = bf_lo(v2); acc1[b * 4 + 1] = bf_hi(v2); acc1[b * 4 + 2] = bf_lo(v3); acc1[b * 4 + 3] = bf_hi(v3);
          }
        } else {
          #pragma unroll
          for (int i = 0; i < 64; i++) { acc0[i] = 0.f; acc1[i] = 0.f; }
        }
        pin_regs(acc0); pin_regs(acc1);
        const int it0 = L * KS_LAYER + T * 16;
        int s = __shfl_sync(~0u, it0 % STAGES, 0); uint32_t ph = (it0 / STAGES) & 1;
        bar_sync(1 + wg, 256);
        int prev = -1;
        #pragma unroll 1
        for (int k = 0; k < nk; k++) {
          mbar_wait(bar_full + 8 * s, ph);
          const uint32_t sa = sbase + s * STAGE_BYTES;
          const uint64_t da = make_desc(sa, 16, 1024), db = make_desc(sa + 16384, 8192, 1024);
          wgmma_fence();
          #pragma unroll
          for (int kk = 0; kk < 4; kk++) {
            wgmma_n128(acc0, da + kk * 2, db + kk * 128, 1);
            wgmma_n128(acc1, da + 512 + kk * 2, db + kk * 128, 1);
          }
          wgmma_commit();
          if (k == nk - 1 && !(L == 1 && T == NT - 1)) bar_arrive(2 - wg, 256);
          wgmma_wait<1>();
          if (prev >= 0 && tid < 2) mbar_arrive_cluster(bar_empty + 8 * prev, tid);
          prev = s;
          if (++s == STAGES) { s = 0; ph ^= 1; }
        }
        wgmma_wait<0>();
        pin_regs(acc0); pin_regs(acc1);
        if (tid < 2) mbar_arrive_cluster(bar_empty + 8 * prev, tid);

        if (resid) {
          uint32_t pk0[32], pk1[32];
          #pragma unroll
          for (int i = 0; i < 32; i++) { pk0[i] = pack_bf16(acc0[2 * i], acc0[2 * i + 1]); pk1[i] = pack_bf16(acc1[2 * i], acc1[2 * i + 1]); }
          const bool last = (L == 1 && T == 11);
          const CUtensorMap* tm = T == 3 ? &P.x1 : (L == 0 ? &P.x2 : &P.out);
          #pragma unroll
          for (int p = 0; p < 2; p++) {
            const uint32_t pb = sbase + SM_S + p * 16384 + st_row * 128;
            #pragma unroll
            for (int i = 0; i < 4; i++) {
              const uint32_t off = ((i * 2 + st_ch) ^ (st_row & 7)) << 4;
              const int q = p * 16 + i * 4;
              stmatrix_x4(pb + off, pk0[q], pk0[q + 1], pk0[q + 2], pk0[q + 3]);
              stmatrix_x4(pb + 8192 + off, pk1[q], pk1[q + 1], pk1[q + 2], pk1[q + 3]);
            }
          }
          fence_async_smem();
          bar_sync(3 + wg, 128);
          if (elect) {
            #pragma unroll
            for (int p = 0; p < 2; p++) {
              tma_store_2d(tm, sbase + SM_S + p * 16384, nj * 128 + p * 64, row0);
              tma_store_2d(tm, sbase + SM_S + p * 16384 + 8192, nj * 128 + p * 64, row0 + 64);
            }
            bulk_commit();
            bulk_wait<0>();
            if (!last) {
              unsigned* c = cnt + (T == 3 ? C_X1 : C_X2) * CNT_STRIDE;
              red_release(c); red_release(c + CNT_STRIDE);
            }
          }
          if (!last) {
            float sm[4] = {0, 0, 0, 0};
            #pragma unroll
            for (int b = 0; b < 16; b++) {
              sm[0] += bf_lo(pk0[2 * b]) + bf_hi(pk0[2 * b]); sm[1] += bf_lo(pk0[2 * b + 1]) + bf_hi(pk0[2 * b + 1]);
              sm[2] += bf_lo(pk1[2 * b]) + bf_hi(pk1[2 * b]); sm[3] += bf_lo(pk1[2 * b + 1]) + bf_hi(pk1[2 * b + 1]);
            }
            float m2[4] = {0, 0, 0, 0}, mean[4];
            #pragma unroll
            for (int r = 0; r < 4; r++) { sm[r] += __shfl_xor_sync(~0u, sm[r], 1); sm[r] += __shfl_xor_sync(~0u, sm[r], 2); mean[r] = sm[r] * (1.f / 128.f); }
            #pragma unroll
            for (int b = 0; b < 16; b++) {
              float d;
              d = bf_lo(pk0[2 * b]) - mean[0]; m2[0] = fmaf(d, d, m2[0]); d = bf_hi(pk0[2 * b]) - mean[0]; m2[0] = fmaf(d, d, m2[0]);
              d = bf_lo(pk0[2 * b + 1]) - mean[1]; m2[1] = fmaf(d, d, m2[1]); d = bf_hi(pk0[2 * b + 1]) - mean[1]; m2[1] = fmaf(d, d, m2[1]);
              d = bf_lo(pk1[2 * b]) - mean[2]; m2[2] = fmaf(d, d, m2[2]); d = bf_hi(pk1[2 * b]) - mean[2]; m2[2] = fmaf(d, d, m2[2]);
              d = bf_lo(pk1[2 * b + 1]) - mean[3]; m2[3] = fmaf(d, d, m2[3]); d = bf_hi(pk1[2 * b + 1]) - mean[3]; m2[3] = fmaf(d, d, m2[3]);
            }
            #pragma unroll
            for (int r = 0; r < 4; r++) { m2[r] += __shfl_xor_sync(~0u, m2[r], 1); m2[r] += __shfl_xor_sync(~0u, m2[r], 2); }
            const int sidx = T == 3 ? L * 2 + 1 : 2;
            float s_ = t == 0 ? sm[0] : t == 1 ? sm[1] : t == 2 ? sm[2] : sm[3];
            float q_ = t == 0 ? m2[0] : t == 1 ? m2[1] : t == 2 ? m2[2] : m2[3];
            g_stats[sidx][row0 + (t >> 1) * 64 + w * 16 + g + (t & 1) * 8][nj] = make_float2(s_, q_);
            bar_sync(3 + wg, 128);
            if (elect) red_release(cnt + (T == 3 ? C_X1S : C_X2S) * CNT_STRIDE);
          }
        } else {
          mbar_wait(T < 3 ? bar_rsA : bar_rsB, L);
          float mu[4], rs[4];
          {
            const uint32_t rb = sbase + SM_RS + (T < 3 ? 0 : 1024) + (w * 16 + g) * 8;
            #pragma unroll
            for (int r = 0; r < 4; r++) { float2 v = lds64(rb + (r & 1) * 64 + (r >> 1) * 512); mu[r] = -v.x; rs[r] = v.y; }
          }
          const uint32_t csb = sbase + SM_CS + (T < 3 ? T : T - 1) * 576 + t * 144;
          #pragma unroll
          for (int i = 0; i < 8; i++) {
            float4 c = lds128(csb + i * 16);
            acc0[i * 8 + 0] = fmaf(mu[0], c.x, acc0[i * 8 + 0]); acc0[i * 8 + 1] = fmaf(mu[0], c.y, acc0[i * 8 + 1]);
            acc0[i * 8 + 2] = fmaf(mu[1], c.x, acc0[i * 8 + 2]); acc0[i * 8 + 3] = fmaf(mu[1], c.y, acc0[i * 8 + 3]);
            acc0[i * 8 + 4] = fmaf(mu[0], c.z, acc0[i * 8 + 4]); acc0[i * 8 + 5] = fmaf(mu[0], c.w, acc0[i * 8 + 5]);
            acc0[i * 8 + 6] = fmaf(mu[1], c.z, acc0[i * 8 + 6]); acc0[i * 8 + 7] = fmaf(mu[1], c.w, acc0[i * 8 + 7]);
            acc1[i * 8 + 0] = fmaf(mu[2], c.x, acc1[i * 8 + 0]); acc1[i * 8 + 1] = fmaf(mu[2], c.y, acc1[i * 8 + 1]);
            acc1[i * 8 + 2] = fmaf(mu[3], c.x, acc1[i * 8 + 2]); acc1[i * 8 + 3] = fmaf(mu[3], c.y, acc1[i * 8 + 3]);
            acc1[i * 8 + 4] = fmaf(mu[2], c.z, acc1[i * 8 + 4]); acc1[i * 8 + 5] = fmaf(mu[2], c.w, acc1[i * 8 + 5]);
            acc1[i * 8 + 6] = fmaf(mu[3], c.z, acc1[i * 8 + 6]); acc1[i * 8 + 7] = fmaf(mu[3], c.w, acc1[i * 8 + 7]);
          }
          if (T >= 4) {
            float cc[4], kk[4];
            #pragma unroll
            for (int r = 0; r < 4; r++) { cc[r] = -rs[r] * LOG2E; kk[r] = rcpf(rs[r] * rs[r]); }
            uint32_t pk0[16], pk1[16];
            #pragma unroll
            for (int i = 0; i < 16; i++) {
              const int r = i & 1;
              float a0 = acc0[2 * i], a1 = acc0[2 * i + 1], b0 = acc1[2 * i], b1 = acc1[2 * i + 1];
              float h0 = a0 * acc0[32 + 2 * i] * rcpf(fmaf(ex2f(a0 * cc[r]), kk[r], kk[r]));
              float h1 = a1 * acc0[33 + 2 * i] * rcpf(fmaf(ex2f(a1 * cc[r]), kk[r], kk[r]));
              float h2 = b0 * acc1[32 + 2 * i] * rcpf(fmaf(ex2f(b0 * cc[2 + r]), kk[2 + r], kk[2 + r]));
              float h3 = b1 * acc1[33 + 2 * i] * rcpf(fmaf(ex2f(b1 * cc[2 + r]), kk[2 + r], kk[2 + r]));
              pk0[i] = pack_bf16(h0, h1); pk1[i] = pack_bf16(h2, h3);
            }
            const uint32_t pb = myS + st_row * 128;
            #pragma unroll
            for (int i = 0; i < 4; i++) {
              const uint32_t off = ((i * 2 + st_ch) ^ (st_row & 7)) << 4;
              stmatrix_x4(pb + off, pk0[i * 4], pk0[i * 4 + 1], pk0[i * 4 + 2], pk0[i * 4 + 3]);
              stmatrix_x4(pb + 8192 + off, pk1[i * 4], pk1[i * 4 + 1], pk1[i * 4 + 2], pk1[i * 4 + 3]);
            }
            fence_async_smem();
            bar_sync(3 + wg, 128);
            if (elect) {
              tma_store_2d(&P.h, myS, nj * 448 + (T - 4) * 64, row0);
              tma_store_2d(&P.h, myS + 8192, nj * 448 + (T - 4) * 64, row0 + 64);
              bulk_commit();
              bulk_wait<0>();
              red_release(cnt + (C_H + T - 4) * CNT_STRIDE);
            }
          } else if (T < 2) {
            float kvd[36];
            #pragma unroll
            for (int i = 0; i < 36; i++) kvd[i] = 0.f;
            pin_regs(kvd);
            #pragma unroll
            for (int h = 0; h < 2; h++) {
              float* acc = h ? acc1 : acc0;
              uint32_t pk[16], pv[16];
              #pragma unroll
              for (int i = 0; i < 16; i++) {
                const float r_ = rs[h * 2 + (i & 1)], rl = r_ * LOG2E;
                pk[i] = pack_bf16(phi(acc[2 * i], r_, rl), phi(acc[2 * i + 1], r_, rl));
                pv[i] = pack_bf16(acc[32 + 2 * i] * r_, acc[33 + 2 * i] * r_);
              }
              if (h == 1) { wgmma_wait<0>(); bar_sync(3 + wg, 128); }
              const uint32_t pb = myS + st_row * 128;
              #pragma unroll
              for (int i = 0; i < 4; i++) {
                const uint32_t off = ((i * 2 + st_ch) ^ (st_row & 7)) << 4;
                stmatrix_x4(pb + off, pk[i * 4], pk[i * 4 + 1], pk[i * 4 + 2], pk[i * 4 + 3]);
                stmatrix_x4(pb + 8192 + off, pv[i * 4], pv[i * 4 + 1], pv[i * 4 + 2], pv[i * 4 + 3]);
              }
              fence_async_smem();
              bar_sync(3 + wg, 128);
              wgmma_fence();
              #pragma unroll
              for (int kk = 0; kk < 4; kk++) {
                const uint32_t va = myS + 8192 + kk * 2048;
                wgmma_n72_tt(kvd, make_desc(myS + kk * 2048, 16, 1024), make_desc(va, sbase + SM_ONES - va, 1024), 1);
              }
              wgmma_commit();
            }
            wgmma_wait<0>();
            pin_regs(kvd);
            float* dst = g_kv[L][nj * 4 + T * 2 + (w >> 1)];
            const int d0 = (w & 1) * 16 + g;
            #pragma unroll
            for (int b = 0; b < 4; b++) {
              float v0 = w < 2 ? kvd[b * 4] : kvd[16 + b * 4], v1 = w < 2 ? kvd[b * 4 + 1] : kvd[17 + b * 4];
              float v2 = w < 2 ? kvd[b * 4 + 2] : kvd[18 + b * 4], v3 = w < 2 ? kvd[b * 4 + 3] : kvd[19 + b * 4];
              red_add_v2(dst + d0 * 32 + b * 8 + t * 2, v0, v1);
              red_add_v2(dst + (d0 + 8) * 32 + b * 8 + t * 2, v2, v3);
            }
            if (t == 0) { red_add(dst + 1024 + d0, kvd[32]); red_add(dst + 1024 + d0 + 8, kvd[34]); }
            bar_sync(3 + wg, 128);
            if (elect) { __threadfence(); red_release(g_kvcnt + (L * 8 + nj) * CNT_STRIDE); }
          } else {
            uint32_t pq0[32], pq1[32];
            #pragma unroll
            for (int i = 0; i < 32; i++) {
              const float ra = rs[i & 1], rb = rs[2 + (i & 1)];
              pq0[i] = pack_bf16(phi(acc0[2 * i], ra, ra * LOG2E), phi(acc0[2 * i + 1], ra, ra * LOG2E));
              pq1[i] = pack_bf16(phi(acc1[2 * i], rb, rb * LOG2E), phi(acc1[2 * i + 1], rb, rb * LOG2E));
            }
            mbar_wait(bar_kv, L);
            #pragma unroll
            for (int hd = 0; hd < 4; hd++) {
              float d0[5][4], d1[5][4];
              #pragma unroll
              for (int nb = 0; nb < 5; nb++) {
                uint32_t bf[4];
                ldmatrix_x4_t(sbase + SM_KV + hd * 2560 + lane * 80 + nb * 16, bf);
                #pragma unroll
                for (int e = 0; e < 4; e++) { d0[nb][e] = 0.f; d1[nb][e] = 0.f; }
                mma_bf16(d0[nb], pq0[hd * 8], pq0[hd * 8 + 1], pq0[hd * 8 + 2], pq0[hd * 8 + 3], bf[0], bf[1]);
                mma_bf16(d1[nb], pq1[hd * 8], pq1[hd * 8 + 1], pq1[hd * 8 + 2], pq1[hd * 8 + 3], bf[0], bf[1]);
                mma_bf16(d0[nb], pq0[hd * 8 + 4], pq0[hd * 8 + 5], pq0[hd * 8 + 6], pq0[hd * 8 + 7], bf[2], bf[3]);
                mma_bf16(d1[nb], pq1[hd * 8 + 4], pq1[hd * 8 + 5], pq1[hd * 8 + 6], pq1[hd * 8 + 7], bf[2], bf[3]);
              }
              const float i0 = rcpf(d0[4][0] + 1e-6f), i1 = rcpf(d0[4][2] + 1e-6f), i2 = rcpf(d1[4][0] + 1e-6f), i3 = rcpf(d1[4][2] + 1e-6f);
              const uint32_t pb = sbase + SM_S + (hd >> 1) * 16384 + st_row * 128;
              #pragma unroll
              for (int i = 0; i < 2; i++) {
                const uint32_t off = (((hd & 1) * 4 + i * 2 + st_ch) ^ (st_row & 7)) << 4;
                stmatrix_x4(pb + off, pack_bf16(d0[2 * i][0] * i0, d0[2 * i][1] * i0), pack_bf16(d0[2 * i][2] * i1, d0[2 * i][3] * i1),
                            pack_bf16(d0[2 * i + 1][0] * i0, d0[2 * i + 1][1] * i0), pack_bf16(d0[2 * i + 1][2] * i1, d0[2 * i + 1][3] * i1));
                stmatrix_x4(pb + 8192 + off, pack_bf16(d1[2 * i][0] * i2, d1[2 * i][1] * i2), pack_bf16(d1[2 * i][2] * i3, d1[2 * i][3] * i3),
                            pack_bf16(d1[2 * i + 1][0] * i2, d1[2 * i + 1][1] * i2), pack_bf16(d1[2 * i + 1][2] * i3, d1[2 * i + 1][3] * i3));
              }
            }
            fence_async_smem();
            bar_sync(3 + wg, 128);
            if (elect) {
              #pragma unroll
              for (int p = 0; p < 2; p++) {
                tma_store_2d(&P.o, sbase + SM_S + p * 16384, nj * 128 + p * 64, row0);
                tma_store_2d(&P.o, sbase + SM_S + p * 16384 + 8192, nj * 128 + p * 64, row0 + 64);
              }
              bulk_commit();
              bulk_wait<0>();
              red_release(cnt + C_O * CNT_STRIDE); red_release(cnt + (C_O + 1) * CNT_STRIDE);
            }
          }
        }
      }
    }
    cluster_sync();
  }
}

typedef CUresult (*EncodeFn)(CUtensorMap*, CUtensorMapDataType, cuuint32_t, void*, const cuuint64_t*, const cuuint64_t*, const cuuint32_t*,
                             const cuuint32_t*, CUtensorMapInterleave, CUtensorMapSwizzle, CUtensorMapL2promotion, CUtensorMapFloatOOBfill);

void make_tmap(EncodeFn enc, CUtensorMap* m, const void* ptr, uint64_t rows, uint64_t cols) {
  cuuint64_t dims[2] = {cols, rows};
  cuuint64_t strides[1] = {cols * 2};
  cuuint32_t box[2] = {64, 64};
  cuuint32_t es[2] = {1, 1};
  enc(m, CU_TENSOR_MAP_DATA_TYPE_BFLOAT16, 2, const_cast<void*>(ptr), dims, strides, box, es, CU_TENSOR_MAP_INTERLEAVE_NONE,
      CU_TENSOR_MAP_SWIZZLE_128B, CU_TENSOR_MAP_L2_PROMOTION_L2_256B, CU_TENSOR_MAP_FLOAT_OOB_FILL_NONE);
}

}

extern "C" void kernel_launch(void* const* d_in, const int* in_sizes, int n_in, void* d_out, int out_size) {
  const __nv_bfloat16* x = (const __nv_bfloat16*)d_in[0];
  const __nv_bfloat16* wqkv = (const __nv_bfloat16*)d_in[1];
  const __nv_bfloat16* wo = (const __nv_bfloat16*)d_in[2];
  const __nv_bfloat16* wg = (const __nv_bfloat16*)d_in[4];
  const __nv_bfloat16* wu = (const __nv_bfloat16*)d_in[5];
  const __nv_bfloat16* wd = (const __nv_bfloat16*)d_in[6];

  void* fn = nullptr;
  cudaDriverEntryPointQueryResult qr;
  cudaGetDriverEntryPoint("cuTensorMapEncodeTiled", &fn, cudaEnableDefault, &qr);
  EncodeFn enc = (EncodeFn)fn;
  void *px1, *px2, *po, *ph;
  cudaGetSymbolAddress(&px1, g_x1); cudaGetSymbolAddress(&px2, g_x2); cudaGetSymbolAddress(&po, g_o); cudaGetSymbolAddress(&ph, g_h);
  Params P;
  make_tmap(enc, &P.x0, x, SEQ, DM); make_tmap(enc, &P.x1, px1, SEQ, DM); make_tmap(enc, &P.x2, px2, SEQ, DM);
  make_tmap(enc, &P.out, d_out, SEQ, DM); make_tmap(enc, &P.o, po, SEQ, DM); make_tmap(enc, &P.h, ph, SEQ, FF);
  make_tmap(enc, &P.wqkv, wqkv, DM, 3 * DM); make_tmap(enc, &P.wo, wo, DM, DM);
  make_tmap(enc, &P.wg, wg, DM, FF); make_tmap(enc, &P.wu, wu, DM, FF); make_tmap(enc, &P.wd, wd, FF, DM);
  P.x0p = x;
  cudaFuncSetAttribute(mega_kernel, cudaFuncAttributeMaxDynamicSharedMemorySize, SM_TOTAL);
  pre_kernel<<<480, 256>>>(x, wqkv, wg, wu);
  mega_kernel<<<128, 384, SM_TOTAL>>>(P);
}
```

```cpp
#include <cuda_runtime.h>
#include <cuda_bf16.h>
#include <cuda.h>
#include <stdint.h>


namespace {

constexpr int SEQ = 2048, DM = 1024, FF = 3584;
constexpr int STAGES = 5;
constexpr int STAGE_BYTES = 32768;
constexpr int TAIL = 4;
constexpr int NT = 12;
constexpr int KS_LAYER = 11 * 16 + 56;

constexpr int SM_S = STAGES * STAGE_BYTES;
constexpr int SM_ONES = SM_S + 32768;
constexpr int SM_KV = SM_ONES + 2048;
constexpr int SM_CS = SM_KV + 16384;
constexpr int SM_RS = SM_CS + 5760;
constexpr int SM_BAR = SM_RS + 2048;
constexpr int SM_TOTAL = SM_BAR + 512;
constexpr uint32_t SM_BASE = 1024;

constexpr int C_O = 0, C_X1 = 2, C_H = 5, C_X2 = 8, C_X0S = 11;
constexpr int CNT_STRIDE = 32;

struct Params {
  CUtensorMap x0, x, out, h, wqkv, wo, wg, wu, wd;
};

__device__ __align__(128) __nv_bfloat16 g_x[SEQ * DM];
__device__ __align__(128) __nv_bfloat16 g_h[SEQ * FF];
__device__ __align__(128) float2 g_stats[4][16][8][128];
__device__ __align__(128) float g_csq[2][8][128];
__device__ __align__(128) float g_csg[8][9][128];
__device__ __align__(128) float g_kv[2][2][8][4224];
__device__ unsigned g_cnt[2 * 16 * 16 * CNT_STRIDE];
__device__ unsigned g_kvcnt[2 * 8 * CNT_STRIDE];
__device__ unsigned g_cqcnt[8 * CNT_STRIDE];
__device__ unsigned g_cgcnt[9 * CNT_STRIDE];
__device__ unsigned g_claim[96];

__device__ __forceinline__ void wgmma_n128(float (&d)[64], uint64_t da, uint64_t db, int scale_d) {
  asm volatile("{\n.reg .pred p;\nsetp.ne.b32 p, %66, 0;\n"
    "wgmma.mma_async.sync.aligned.m64n128k16.f32.bf16.bf16 {%0, %1, %2, %3, %4, %5, %6, %7, %8, %9, %10, %11, %12, %13, %14, %15, %16, %17, %18, %19, %20, %21, %22, %23, %24, %25, %26, %27, %28, %29, %30, %31, %32, %33, %34, %35, %36, %37, %38, %39, %40, %41, %42, %43, %44, %45, %46, %47, %48, %49, %50, %51, %52, %53, %54, %55, %56, %57, %58, %59, %60, %61, %62, %63}, %64, %65, p, 1, 1, 0, 1;\n}\n"
    : "+f"(d[0]), "+f"(d[1]), "+f"(d[2]), "+f"(d[3]), "+f"(d[4]), "+f"(d[5]), "+f"(d[6]), "+f"(d[7]), "+f"(d[8]), "+f"(d[9]), "+f"(d[10]), "+f"(d[11]), "+f"(d[12]), "+f"(d[13]), "+f"(d[14]), "+f"(d[15]), "+f"(d[16]), "+f"(d[17]), "+f"(d[18]), "+f"(d[19]), "+f"(d[20]), "+f"(d[21]), "+f"(d[22]), "+f"(d[23]), "+f"(d[24]), "+f"(d[25]), "+f"(d[26]), "+f"(d[27]), "+f"(d[28]), "+f"(d[29]), "+f"(d[30]), "+f"(d[31]), "+f"(d[32]), "+f"(d[33]), "+f"(d[34]), "+f"(d[35]), "+f"(d[36]), "+f"(d[37]), "+f"(d[38]), "+f"(d[39]), "+f"(d[40]), "+f"(d[41]), "+f"(d[42]), "+f"(d[43]), "+f"(d[44]), "+f"(d[45]), "+f"(d[46]), "+f"(d[47]), "+f"(d[48]), "+f"(d[49]), "+f"(d[50]), "+f"(d[51]), "+f"(d[52]), "+f"(d[53]), "+f"(d[54]), "+f"(d[55]), "+f"(d[56]), "+f"(d[57]), "+f"(d[58]), "+f"(d[59]), "+f"(d[60]), "+f"(d[61]), "+f"(d[62]), "+f"(d[63])
    : "l"(da), "l"(db), "r"(scale_d));
}

__device__ __forceinline__ void wgmma_n72_tt(float (&d)[36], uint64_t da, uint64_t db, int scale_d) {
  asm volatile("{\n.reg .pred p;\nsetp.ne.b32 p, %38, 0;\n"
    "wgmma.mma_async.sync.aligned.m64n72k16.f32.bf16.bf16 {%0, %1, %2, %3, %4, %5, %6, %7, %8, %9, %10, %11, %12, %13, %14, %15, %16, %17, %18, %19, %20, %21, %22, %23, %24, %25, %26, %27, %28, %29, %30, %31, %32, %33, %34, %35}, %36, %37, p, 1, 1, 1, 1;\n}\n"
    : "+f"(d[0]), "+f"(d[1]), "+f"(d[2]), "+f"(d[3]), "+f"(d[4]), "+f"(d[5]), "+f"(d[6]), "+f"(d[7]), "+f"(d[8]), "+f"(d[9]), "+f"(d[10]), "+f"(d[11]), "+f"(d[12]), "+f"(d[13]), "+f"(d[14]), "+f"(d[15]), "+f"(d[16]), "+f"(d[17]), "+f"(d[18]), "+f"(d[19]), "+f"(d[20]), "+f"(d[21]), "+f"(d[22]), "+f"(d[23]), "+f"(d[24]), "+f"(d[25]), "+f"(d[26]), "+f"(d[27]), "+f"(d[28]), "+f"(d[29]), "+f"(d[30]), "+f"(d[31]), "+f"(d[32]), "+f"(d[33]), "+f"(d[34]), "+f"(d[35])
    : "l"(da), "l"(db), "r"(scale_d));
}

__device__ __forceinline__ uint32_t smem_u32(const void* p) { return (uint32_t)__cvta_generic_to_shared(p); }
__device__ __forceinline__ void mbar_init(uint32_t bar, uint32_t count) { asm volatile("mbarrier.init.shared::cta.b64 [%0], %1;" :: "r"(bar), "r"(count)); }
__device__ __forceinline__ void mbar_expect_tx(uint32_t bar, uint32_t bytes) { asm volatile("mbarrier.arrive.expect_tx.shared::cta.b64 _, [%0], %1;" :: "r"(bar), "r"(bytes) : "memory"); }
__device__ __forceinline__ void mbar_arrive(uint32_t bar) { asm volatile("mbarrier.arrive.shared::cta.b64 _, [%0];" :: "r"(bar) : "memory"); }
__device__ __forceinline__ bool mbar_test_wait(uint32_t bar, uint32_t parity) {
  uint32_t ok;
  asm volatile("{\n.reg .pred p;\nmbarrier.test_wait.parity.shared::cta.b64 p, [%1], %2;\nselp.u32 %0, 1, 0, p;\n}\n" : "=r"(ok) : "r"(bar), "r"(parity) : "memory");
  return ok;
}
__device__ __forceinline__ bool mbar_try_wait_park(uint32_t bar, uint32_t parity) {
  uint32_t ok;
  asm volatile("{\n.reg .pred p;\nmbarrier.try_wait.parity.shared::cta.b64 p, [%1], %2, 4000;\nselp.u32 %0, 1, 0, p;\n}\n" : "=r"(ok) : "r"(bar), "r"(parity) : "memory");
  return ok;
}
__device__ __forceinline__ void mbar_wait(uint32_t bar, uint32_t parity) {
  int it = 0;
  while (!mbar_try_wait_park(bar, parity)) { if (++it > (1 << 20)) __trap(); }
}
__device__ __forceinline__ void mbar_wait_spin(uint32_t bar, uint32_t parity) {
  uint32_t ok; int it = 0;
  do {
    asm volatile("{\n.reg .pred p;\nmbarrier.try_wait.parity.shared::cta.b64 p, [%1], %2;\nselp.u32 %0, 1, 0, p;\n}\n" : "=r"(ok) : "r"(bar), "r"(parity) : "memory");
    if (++it > (1 << 22)) __trap();
  } while (!ok);
}
__device__ __forceinline__ void mbar_wait_c(uint32_t bar, uint32_t parity) {
  while (!mbar_try_wait_park(bar, parity)) {}
}
__device__ __forceinline__ unsigned ld_flag(const unsigned* p) { unsigned v; asm volatile("ld.relaxed.gpu.global.u32 %0, [%1];" : "=r"(v) : "l"(p) : "memory"); return v; }
__device__ __forceinline__ void fence_gpu() { asm volatile("fence.acq_rel.gpu;" ::: "memory"); }
__device__ __forceinline__ void fence_acquire() { asm volatile("fence.acquire.gpu;" ::: "memory"); }
__device__ __forceinline__ void flag_add(unsigned* p) { asm volatile("red.relaxed.gpu.global.add.u32 [%0], 1;" :: "l"(p) : "memory"); }
__device__ __forceinline__ void bulk_to_peer(uint32_t dst, uint32_t src, uint32_t bytes, uint32_t bar, uint32_t peer) {
  asm volatile("{\n.reg .b32 rd, rb;\nmapa.shared::cluster.u32 rd, %0, %4;\nmapa.shared::cluster.u32 rb, %3, %4;\n"
               "cp.async.bulk.shared::cluster.shared::cta.mbarrier::complete_tx::bytes [rd], [%1], %2, [rb];\n}\n"
               :: "r"(dst), "r"(src), "r"(bytes), "r"(bar), "r"(peer) : "memory");
}
__device__ __forceinline__ void sts128(uint32_t a, float x, float y, float z, float w) { asm volatile("st.shared.v4.f32 [%0], {%1, %2, %3, %4};" :: "r"(a), "f"(x), "f"(y), "f"(z), "f"(w) : "memory"); }
__device__ __forceinline__ uint4 lds128u(uint32_t a) { uint4 v; asm volatile("ld.shared.v4.u32 {%0, %1, %2, %3}, [%4];" : "=r"(v.x), "=r"(v.y), "=r"(v.z), "=r"(v.w) : "r"(a) : "memory"); return v; }
__device__ __forceinline__ void ldmatrix_x4(uint32_t addr, uint32_t (&r)[4]) {
  asm volatile("ldmatrix.sync.aligned.m8n8.x4.shared.b16 {%0, %1, %2, %3}, [%4];" : "=r"(r[0]), "=r"(r[1]), "=r"(r[2]), "=r"(r[3]) : "r"(addr) : "memory");
}
__device__ __forceinline__ void sts64(uint32_t a, float x, float y) { asm volatile("st.shared.v2.f32 [%0], {%1, %2};" :: "r"(a), "f"(x), "f"(y) : "memory"); }
__device__ __forceinline__ void flag_wait(const unsigned* p, unsigned target) {
  int it = 0;
  while ((int)(ld_flag(p) - target) < 0) { __nanosleep(200); if (++it > (1 << 21)) __trap(); }
  fence_acquire();
}
__device__ __forceinline__ void flag_wait_fast(const unsigned* p, unsigned target) {
  int it = 0;
  while ((int)(ld_flag(p) - target) < 0) { if (++it > (1 << 22)) __trap(); }
}
__device__ __forceinline__ void tma_load_2d(uint32_t dst, const CUtensorMap* tm, int c0, int c1, uint32_t bar) {
  asm volatile("cp.async.bulk.tensor.2d.shared::cluster.global.mbarrier::complete_tx::bytes [%0], [%1, {%3, %4}], [%2];"
    :: "r"(dst), "l"(tm), "r"(bar), "r"(c0), "r"(c1) : "memory");
}
__device__ __forceinline__ void tma_load_2d_mc(uint32_t dst, const CUtensorMap* tm, int c0, int c1, uint32_t bar, uint16_t mask) {
  asm volatile("cp.async.bulk.tensor.2d.shared::cluster.global.mbarrier::complete_tx::bytes.multicast::cluster [%0], [%1, {%3, %4}], [%2], %5;"
    :: "r"(dst), "l"(tm), "r"(bar), "r"(c0), "r"(c1), "h"(mask) : "memory");
}
__device__ __forceinline__ void tma_store_2d(const CUtensorMap* tm, uint32_t src, int c0, int c1) {
  asm volatile("cp.async.bulk.tensor.2d.global.shared::cta.bulk_group [%0, {%2, %3}], [%1];" :: "l"(tm), "r"(src), "r"(c0), "r"(c1) : "memory");
}
__device__ __forceinline__ void bulk_commit() { asm volatile("cp.async.bulk.commit_group;" ::: "memory"); }
template <int N> __device__ __forceinline__ void bulk_wait() { asm volatile("cp.async.bulk.wait_group %0;" :: "n"(N) : "memory"); }
__device__ __forceinline__ void fence_async_smem() { asm volatile("fence.proxy.async.shared::cta;" ::: "memory"); }
__device__ __forceinline__ void fence_async_global() { asm volatile("fence.acquire.gpu;\nfence.proxy.async.global;" ::: "memory"); }
__device__ __forceinline__ void wgmma_fence() { asm volatile("wgmma.fence.sync.aligned;" ::: "memory"); }
__device__ __forceinline__ void wgmma_commit() { asm volatile("wgmma.commit_group.sync.aligned;" ::: "memory"); }
template <int N> __device__ __forceinline__ void wgmma_wait() { asm volatile("wgmma.wait_group.sync.aligned %0;" :: "n"(N) : "memory"); }
__device__ __forceinline__ uint64_t make_desc(uint32_t addr, uint32_t lbo, uint32_t sbo) {
  return (uint64_t)((addr & 0x3FFFF) >> 4) | ((uint64_t)(lbo >> 4) << 16) | ((uint64_t)(sbo >> 4) << 32) | (1ull << 62);
}
__device__ __forceinline__ uint64_t desc64(uint32_t lo) { return (uint64_t)lo | (0x40000040ull << 32); }
__device__ __forceinline__ void cluster_sync_relaxed() {
  asm volatile("barrier.cluster.arrive.relaxed.aligned;\nbarrier.cluster.wait.acquire.aligned;" ::: "memory");
}
__device__ __forceinline__ uint32_t cluster_ctarank() { uint32_t r; asm volatile("mov.u32 %0, %%cluster_ctarank;" : "=r"(r)); return r; }
__device__ __forceinline__ void bar_sync(int id, int n) { asm volatile("bar.sync %0, %1;" :: "r"(id), "r"(n) : "memory"); }
__device__ __forceinline__ void bar_arrive(int id, int n) { asm volatile("bar.arrive %0, %1;" :: "r"(id), "r"(n) : "memory"); }
__device__ __forceinline__ void stmatrix_x4(uint32_t addr, uint32_t r0, uint32_t r1, uint32_t r2, uint32_t r3) {
  asm volatile("stmatrix.sync.aligned.m8n8.x4.shared.b16 [%0], {%1, %2, %3, %4};" :: "r"(addr), "r"(r0), "r"(r1), "r"(r2), "r"(r3) : "memory");
}
__device__ __forceinline__ void ldmatrix_x4_t(uint32_t addr, uint32_t (&r)[4]) {
  asm volatile("ldmatrix.sync.aligned.m8n8.x4.trans.shared.b16 {%0, %1, %2, %3}, [%4];" : "=r"(r[0]), "=r"(r[1]), "=r"(r[2]), "=r"(r[3]) : "r"(addr) : "memory");
}
__device__ __forceinline__ void mma_bf16(float (&d)[4], uint32_t a0, uint32_t a1, uint32_t a2, uint32_t a3, uint32_t b0, uint32_t b1) {
  asm("mma.sync.aligned.m16n8k16.row.col.f32.bf16.bf16.f32 {%0, %1, %2, %3}, {%4, %5, %6, %7}, {%8, %9}, {%0, %1, %2, %3};"
    : "+f"(d[0]), "+f"(d[1]), "+f"(d[2]), "+f"(d[3]) : "r"(a0), "r"(a1), "r"(a2), "r"(a3), "r"(b0), "r"(b1));
}
__device__ __forceinline__ void mma_bf16_v(float (&d)[4], uint32_t a0, uint32_t a1, uint32_t a2, uint32_t a3, uint32_t b0, uint32_t b1) {
  asm volatile("mma.sync.aligned.m16n8k16.row.col.f32.bf16.bf16.f32 {%0, %1, %2, %3}, {%4, %5, %6, %7}, {%8, %9}, {%0, %1, %2, %3};"
    : "+f"(d[0]), "+f"(d[1]), "+f"(d[2]), "+f"(d[3]) : "r"(a0), "r"(a1), "r"(a2), "r"(a3), "r"(b0), "r"(b1));
}
__device__ __forceinline__ uint32_t pack_bf16(float a, float b) { uint32_t r; asm("cvt.rn.bf16x2.f32 %0, %1, %2;" : "=r"(r) : "f"(b), "f"(a)); return r; }
__device__ __forceinline__ float bf_lo(uint32_t v) { return __uint_as_float(v << 16); }
__device__ __forceinline__ float bf_hi(uint32_t v) { return __uint_as_float(v & 0xffff0000u); }
__device__ __forceinline__ float ex2f(float x) { float r; asm("ex2.approx.ftz.f32 %0, %1;" : "=f"(r) : "f"(x)); return r; }
__device__ __forceinline__ float rcpf(float x) { float r; asm("rcp.approx.ftz.f32 %0, %1;" : "=f"(r) : "f"(x)); return r; }
__device__ __forceinline__ float4 lds128(uint32_t a) { float4 v; asm volatile("ld.shared.v4.f32 {%0, %1, %2, %3}, [%4];" : "=f"(v.x), "=f"(v.y), "=f"(v.z), "=f"(v.w) : "r"(a)); return v; }
__device__ __forceinline__ float2 lds64(uint32_t a) { float2 v; asm volatile("ld.shared.v2.f32 {%0, %1}, [%2];" : "=f"(v.x), "=f"(v.y) : "r"(a)); return v; }

__device__ __forceinline__ void red_add_v4(float* p, float a, float b, float c, float d) { asm volatile("red.relaxed.gpu.global.add.v4.f32 [%0], {%1, %2, %3, %4};" :: "l"(p), "f"(a), "f"(b), "f"(c), "f"(d) : "memory"); }
__device__ __forceinline__ void red_add(float* p, float a) { asm volatile("red.relaxed.gpu.global.add.f32 [%0], %1;" :: "l"(p), "f"(a) : "memory"); }
template <int N> __device__ __forceinline__ void pin_regs(float (&d)[N]) {
  #pragma unroll
  for (int i = 0; i < N; i++) asm volatile("" : "+f"(d[i]) :: "memory");
}

constexpr float LOG2E = 1.4426950408889634f;

__device__ __forceinline__ float phi(float y, float rs, float rsl) {
  const float a = fmaf(y, rs, 1.000001f);
  const float b = ex2f(y * rsl) + 1e-6f;
  return y > 0.f ? a : b;
}

__device__ __forceinline__ uint64_t chunk_order(int nj) {
  const uint32_t own = nj * 2, peer = (nj ^ 1) * 2;
  uint64_t o = own | ((own + 1) << 4) | (peer << 8) | ((peer + 1) << 12);
  #pragma unroll
  for (int i = 0; i < 6; i++) {
    const uint64_t c = ((((nj >> 1) + 1 + (i >> 1)) & 3) << 2) | ((i & 1) << 1);
    o |= (c << (16 + 4 * i)) | ((c + 1) << (40 + 4 * i));
  }
  return o;
}
__device__ __forceinline__ bool elect_one() {
  uint32_t p;
  asm volatile("{\n.reg .pred q;\nelect.sync _|q, 0xffffffff;\nselp.u32 %0, 1, 0, q;\n}\n" : "=r"(p));
  return p;
}

__device__ __forceinline__ void b_tile(const Params& P, int T, int nj, const CUtensorMap*& t0, const CUtensorMap*& t1, int& c0, int& c1) {
  if (T < 2) { t0 = t1 = &P.wqkv; c0 = 1024 + nj * 128 + T * 64; c1 = c0 + 1024; }
  else if (T == 2) { t0 = t1 = &P.wqkv; c0 = nj * 128; c1 = c0 + 64; }
  else if (T == 3) { t0 = t1 = &P.wo; c0 = nj * 128; c1 = c0 + 64; }
  else if (T < 11) { t0 = &P.wg; t1 = &P.wu; c0 = c1 = nj * 448 + (T - 4) * 64; }
  else { t0 = t1 = &P.wd; c0 = nj * 128; c1 = c0 + 64; }
}
__device__ __forceinline__ bool is_pair(int L, int T) { return T == 4 || (T == 0 && L == 1); }
__device__ __forceinline__ void add8(float (&s)[8], const uint4& v) {
  s[0] += bf_lo(v.x); s[1] += bf_hi(v.x); s[2] += bf_lo(v.y); s[3] += bf_hi(v.y);
  s[4] += bf_lo(v.z); s[5] += bf_hi(v.z); s[6] += bf_lo(v.w); s[7] += bf_hi(v.w);
}

__device__ __forceinline__ void helper_cta(int q, unsigned epoch, uint32_t sbase, uint32_t bar_full, uint32_t bar_empty) {
  const int tid = threadIdx.x;
  const int blk = tid >> 6, r0 = (tid >> 3) & 7, cg = tid & 7;
  const uint32_t rd = sbase + blk * 8192 + r0 * 128 + ((cg ^ r0) << 4);
  const uint32_t red = sbase + SM_S;
  int s = 0; uint32_t ph = 1;
  #pragma unroll 1
  for (int t = 0; t < 9; t++) {
    float a8[8] = {0, 0, 0, 0, 0, 0, 0, 0};
    #pragma unroll 1
    for (int k = 0; k < 16; k++) {
      mbar_wait_c(bar_full + 8 * s, ph);
      uint4 v[8];
      #pragma unroll
      for (int i = 0; i < 8; i++) v[i] = lds128u(rd + s * STAGE_BYTES + i * 1024);
      #pragma unroll
      for (int i = 0; i < 8; i++) add8(a8, v[i]);
      bar_sync(3 + (tid >> 7), 128);
      if ((tid & 127) == 0) mbar_arrive(bar_empty + 8 * s);
      if (++s == STAGES) { s = 0; ph ^= 1; }
    }
    const uint32_t rb = red + (t & 1) * 8192;
    sts128(rb + tid * 32, a8[0], a8[1], a8[2], a8[3]); sts128(rb + tid * 32 + 16, a8[4], a8[5], a8[6], a8[7]);
    bar_sync(3 + (tid >> 7), 128);
    float a = 0;
    #pragma unroll
    for (int r = 0; r < 8; r++) { float x; asm volatile("ld.shared.f32 %0, [%1];" : "=f"(x) : "r"(rb + (blk * 512 + r * 64 + (tid & 63)) * 4) : "memory"); a += x; }
    g_csg[2 * q + (tid >> 7)][t][tid & 127] = a;
    __syncwarp();
    if ((tid & 31) == 0) { fence_gpu(); flag_add(g_cgcnt + t * CNT_STRIDE); }
    __syncwarp();
  }
  const int nxt = (epoch + 1) & 1;
  for (int i = q * 256 + tid; i < 2 * 8 * 4224 / 4; i += 4 * 256) ((float4*)&g_kv[nxt][0][0][0])[i] = make_float4(0.f, 0.f, 0.f, 0.f);
  for (int i = q * 256 + tid; i < 8 * 128 / 4; i += 4 * 256) ((float4*)&g_csq[nxt][0][0])[i] = make_float4(0.f, 0.f, 0.f, 0.f);
}

__device__ __forceinline__ void startup_loads(const Params& P, uint32_t sbase, uint32_t bar, int mi, int nj) {
  mbar_expect_tx(bar, 49152);
  #pragma unroll 1
  for (int i = 0; i < 4; i++) tma_load_2d(sbase + SM_S + i * 8192, &P.x0, nj * 128 + (i >> 1) * 64, mi * 128 + (i & 1) * 64, bar);
  tma_load_2d(sbase + SM_KV, &P.wqkv, 1024 + nj * 128, mi * 64, bar);
  tma_load_2d(sbase + SM_KV + 8192, &P.wqkv, 2048 + nj * 128, mi * 64, bar);
}

__device__ __forceinline__ int preferred_role() {
  if (gridDim.x != 132) return (blockIdx.x >> 1) + (gridDim.x == 4 ? 64 : 0);
  unsigned smid; asm volatile("mov.u32 %0, %%smid;" : "=r"(smid));
  const int tpc = smid >> 1;
  if (tpc < 32) return (tpc & 7) * 8 + (tpc >> 3);
  if (tpc < 60) return (1 + (tpc - 32) % 7) * 8 + 4 + (tpc - 32) / 7;
  if (tpc < 62) return 64 + (tpc - 60);
  return 4 + ((tpc - 62) & 3);
}

__global__ void __cluster_dims__(2, 1, 1) __launch_bounds__(384, 1) mega_kernel(const __nv_bfloat16* __restrict__ wqkv_p, const __nv_bfloat16* __restrict__ x0_p, const __grid_constant__ Params P) {
  extern __shared__ __align__(1024) uint8_t smem_raw[];
  const uint32_t sbase = smem_u32(smem_raw);
  const uint32_t bar_full = sbase + SM_BAR, bar_empty = bar_full + 8 * STAGES;
  const uint32_t bar_rsA = bar_empty + 8 * STAGES, bar_rsB = bar_rsA + 8, bar_done = bar_rsB + 8;
  const uint32_t bar_res = bar_done + 8, bar_res2 = bar_res + 8, bar_sig = bar_res2 + 8, bar_free = bar_sig + 32, bar_cs = bar_free + 32;
  const uint32_t bar_role = bar_cs + 80, bar_pref = bar_role + 8, bar_go = bar_pref + 8, bar_peer = bar_go + 16, sm_role = bar_peer + 16, bar_emptyB = sm_role + 16;
  const int warp = __shfl_sync(0xffffffff, threadIdx.x >> 5, 0), lane = threadIdx.x & 31;
  const uint32_t rank = cluster_ctarank();
  const bool claimed = gridDim.x == 132;
  const int pref = preferred_role();
  const int pmi = ((pref >> 5) & 1) * 8 + (pref & 7), pnj = ((pref >> 3) & 3) * 2 + rank;

  unsigned claim_old = 0, claim_epoch = 0;
  if (threadIdx.x == 320) {
    #pragma unroll
    for (int s = 0; s < STAGES; s++) mbar_init(bar_full + 8 * s, 2);
    mbar_init(bar_res, 1);
    asm volatile("fence.mbarrier_init.release.cluster;" ::: "memory");
    fence_async_smem();
  } else if (threadIdx.x == 352) {
    if (rank == 0) {
      claim_epoch = ld_flag(&g_claim[88]);
      if (claimed) claim_old = atomicExch(&g_claim[pref], 1u);
    }
  } else if (threadIdx.x == 0) {
    if ((sbase & 0xFFFFFF) != SM_BASE) __trap();
    for (int s = 0; s < STAGES; s++) { mbar_init(bar_empty + 8 * s, 2); mbar_init(bar_emptyB + 8 * s, 1); }
    mbar_init(bar_rsA, 128); mbar_init(bar_rsB, 128); mbar_init(bar_done, 2); mbar_init(bar_res2, 1);
    for (int i = 0; i < 4; i++) { mbar_init(bar_sig + 8 * i, 128); mbar_init(bar_free + 8 * i, 1); }
    for (int i = 0; i < 10; i++) mbar_init(bar_cs + 8 * i, 1);
    mbar_init(bar_role, 1); mbar_init(bar_pref, 1); mbar_init(bar_go, 1); mbar_init(bar_go + 8, 128); mbar_init(bar_peer, 1); mbar_init(bar_peer + 8, 1);
    mbar_expect_tx(bar_role, 8); mbar_expect_tx(bar_pref, 4);
    asm volatile("fence.mbarrier_init.release.cluster;" ::: "memory");
  }
  __syncwarp();
  asm volatile("barrier.cluster.arrive.relaxed.aligned;" ::: "memory");
  if (threadIdx.x == 320) {
    #pragma unroll 1
    for (int k = 0; k < STAGES; k++) {
      const uint32_t st = sbase + k * STAGE_BYTES, bar = bar_full + 8 * k;
      mbar_expect_tx(bar, 32768); mbar_arrive(bar);
      tma_load_2d(st, &P.x0, k * 64, pmi * 128, bar);
      tma_load_2d(st + 16384, &P.wqkv, 1024 + pnj * 128, k * 64, bar);
      tma_load_2d(st + 8192, &P.x0, k * 64, pmi * 128 + 64, bar);
      tma_load_2d(st + 24576, &P.wqkv, 2048 + pnj * 128, k * 64, bar);
    }
  }
  __syncwarp();
  asm volatile("barrier.cluster.wait.acquire.aligned;" ::: "memory");
  if (threadIdx.x == 352) {
    if (rank == 1) {
      asm volatile("{\n.reg .b32 ra, rb;\nmapa.shared::cluster.u32 ra, %0, 0;\nmapa.shared::cluster.u32 rb, %1, 0;\n"
                   "st.async.weak.shared::cluster.mbarrier::complete_tx::bytes.u32 [ra], %2, [rb];\n}\n"
                   :: "r"(sm_role + 8), "r"(bar_pref), "r"(pref) : "memory");
    } else {
      int r = pref;
      if (claimed) {
        asm volatile("red.relaxed.gpu.global.add.u32 [%0], %1;" :: "l"(&g_claim[80]), "r"(1 + (claim_old >> 1)) : "memory");
        if (claim_old != 0) {
          flag_wait(&g_claim[80], (claim_epoch + 1) * 66);
          #pragma unroll 1
          for (r = 0; r < 65; r++) if (atomicExch(&g_claim[r], 1u) == 0) break;
          if (r == 65) atomicExch(&g_claim[65], 1u);
        }
      }
      mbar_wait(bar_pref, 0);
      int pref1; asm volatile("ld.shared.u32 %0, [%1];" : "=r"(pref1) : "r"(sm_role + 8) : "memory");
      if (r != pref || r != pref1 || r >= 64) r |= 256;
      #pragma unroll
      for (int c = 0; c < 2; c++)
        asm volatile("{\n.reg .b32 ra, rb;\nmapa.shared::cluster.u32 ra, %0, %4;\nmapa.shared::cluster.u32 rb, %1, %4;\n"
                     "st.async.weak.shared::cluster.mbarrier::complete_tx::bytes.v2.u32 [ra], {%2, %3}, [rb];\n}\n"
                     :: "r"(sm_role), "r"(bar_role), "r"(r), "r"(claim_epoch), "r"(c) : "memory");
    }
  }
  if (warp == 7) {
    #pragma unroll 1
    for (int kp = 2; kp < 8; kp++) {
      asm volatile("prefetch.global.L2 [%0];" :: "l"(x0_p + (size_t)(pmi * 128 + pnj * 16 + (lane >> 1)) * DM + kp * 128 + (lane & 1) * 64) : "memory");
      if (lane < 16) asm volatile("prefetch.global.L2 [%0];" :: "l"(wqkv_p + (size_t)(kp * 128 + pmi * 8 + (lane >> 1)) * (3 * DM) + 1024 + (lane & 1) * 1024 + pnj * 128) : "memory");
      __nanosleep(200);
    }
    if (lane == 0) startup_loads(P, sbase, bar_res, pmi, pnj);
  }
  __syncwarp();

#define GET_ROLE(WAIT)                                                                                              \
  int role; unsigned epoch;                                                                                         \
  WAIT(bar_role, 0);                                                                                                \
  asm volatile("ld.shared.v2.u32 {%0, %1}, [%2];" : "=r"(role), "=r"(epoch) : "r"(sm_role) : "memory");            \
  role = __shfl_sync(~0u, role, 0); epoch = __shfl_sync(~0u, epoch, 0);                                            \
  const int roff = (role >> 8) ? STAGES : 0;                                                                        \
  role &= 255;                                                                                                      \
  const int mi = (role >> 5) * 8 + (role & 7), nj = ((role >> 3) & 3) * 2 + rank;                                   \
  const int row0 = mi * 128;

  if (warp >= 8) {
    asm volatile("setmaxnreg.dec.sync.aligned.u32 56;");
    __syncwarp();
    GET_ROLE(mbar_wait)
    const unsigned t8 = (epoch + 1) * 8;
    unsigned* const cnt_base = g_cnt + mi * 16 * CNT_STRIDE;
    const bool l0 = lane == 0;
    const uint64_t ord_fresh = chunk_order(nj);
    if (warp == 10 && role < 64) {
      int s = 0; uint32_t ph = 0;
      #pragma unroll 1
      for (int k = STAGES - roff; k < 16; k++) {
        mbar_wait_spin(bar_empty + 8 * s, ph);
        if (elect_one()) {
          const uint32_t st = sbase + s * STAGE_BYTES, bar = bar_full + 8 * s;
          mbar_expect_tx(bar, 32768); mbar_arrive(bar);
          tma_load_2d_mc(st + rank * 8192, &P.x0, k * 64, row0 + rank * 64, bar, 3);
          tma_load_2d(st + 16384, &P.wqkv, 1024 + nj * 128, k * 64, bar);
          tma_load_2d(st + 24576, &P.wqkv, 2048 + nj * 128, k * 64, bar);
        }
        if (++s == STAGES) { s = 0; ph ^= 1; }
      }
      bar_arrive(8, 96);
    }
    if (role >= 64) {
      if (warp < 10) {
        int s = 0; uint32_t ph = 0;
        const int cgp = ((role - 64) * 2 + rank) * 2 + (warp - 8);
        #pragma unroll 1
        for (int i = 0; i < 9 * 16; i++) {
          const CUtensorMap *t0, *t1; int c0, c1;
          b_tile(P, (i < 32 ? 1 : 2) + (i >> 4), cgp, t0, t1, c0, c1);
          mbar_wait(bar_empty + 8 * s, ph);
          if (elect_one()) {
            const uint32_t dst = sbase + s * STAGE_BYTES + (warp - 8) * 16384;
            mbar_expect_tx(bar_full + 8 * s, 16384);
            tma_load_2d(dst, t0, c0, (i & 15) * 64, bar_full + 8 * s);
            tma_load_2d(dst + 8192, t1, c1, (i & 15) * 64, bar_full + 8 * s);
          }
          if (++s == STAGES) { s = 0; ph ^= 1; }
        }
      } else if (warp == 11) {
        mbar_wait(bar_done, 0);
        if (claimed && rank == 0) {
          flag_wait(g_kvcnt, (epoch + 1) * 16);
          if (l0) g_claim[role] = 0;
        }
      }
    } else if (warp == 8) {
      int s = (16 + roff) % STAGES; uint32_t ph = (((16 + roff) / STAGES) & 1) ^ 1;
      bool gate = true;
      const int arow = row0 + rank * 64;
      auto step = [&](const CUtensorMap* tm, int chunk, bool load) {
        if (gate) { bar_sync(8, 96); gate = false; }
        mbar_wait_spin(bar_empty + 8 * s, ph);
        if (elect_one()) {
          mbar_expect_tx(bar_full + 8 * s, 16384);
          if (load) tma_load_2d_mc(sbase + s * STAGE_BYTES + rank * 8192, tm, chunk * 64, arow, bar_full + 8 * s, 3);
        }
        if (++s == STAGES) { s = 0; ph ^= 1; }
      };
      auto skip = [&]() { if (++s == STAGES) { s = 0; ph ^= 1; } };
      uint32_t go_ph = 0, st_ph = 0;
      unsigned hpeek = 0;
      #pragma unroll 1
      for (int L = 0; L < 2; L++) {
        #pragma unroll 1
        for (int T = L == 0; T < 11; T++) {
          const CUtensorMap* tm = T == 3 ? &P.h : (T < 3 && L == 0) ? &P.x0 : &P.x;
          const bool pair = is_pair(L, T);
          if (pair || T == 3) {
            const unsigned* dep = cnt_base + (T == 0 ? C_X2 : L * 256 + (T == 3 ? C_O : C_X1)) * CNT_STRIDE;
            const uint64_t ord0 = ord_fresh >> 16;
            const int s0 = s;
            if (T == 3) {
              #pragma unroll 1
              for (int p = 0; p < 2; p++) {
                mbar_wait(bar_empty + 8 * s, ph);
                if (elect_one()) {
                  const CUtensorMap* tr = L == 0 ? &P.x0 : &P.x;
                  if (p == 0) mbar_expect_tx(bar_res2, 32768);
                  tma_load_2d(sbase + s * STAGE_BYTES, tr, nj * 128 + p * 64, row0, bar_res2);
                  tma_load_2d(sbase + s * STAGE_BYTES + 8192, tr, nj * 128 + p * 64, row0 + 64, bar_res2);
                }
                skip();
              }
              step(tm, 0, false); step(tm, 0, false);
              mbar_wait(bar_go, go_ph); go_ph ^= 1;
              if (elect_one()) bulk_to_peer(sbase + ((s0 + 2) % STAGES) * STAGE_BYTES, sbase + SM_S, 16384, bar_full + 8 * ((s0 + 2) % STAGES), rank ^ 1);
              __syncwarp();
              mbar_wait(bar_go + 8, st_ph); st_ph ^= 1;
              if (lane < 2) mbar_arrive(bar_full + 8 * ((s0 + lane) % STAGES));
              __syncwarp();
              if (elect_one()) bulk_to_peer(sbase + ((s0 + 3) % STAGES) * STAGE_BYTES, sbase + SM_S + 16384, 16384, bar_full + 8 * ((s0 + 3) % STAGES), rank ^ 1);
            } else {
              #pragma unroll 1
              for (int k = 0; k < 4; k++) { mbar_wait(bar_empty + 8 * s, ph); skip(); }
              mbar_wait(bar_go, go_ph);
              if (elect_one()) {
                #pragma unroll
                for (int p = 0; p < 2; p++) {
                  mbar_expect_tx(bar_peer + 8 * p, 16384);
                  bulk_to_peer(sbase + ((s0 + 6 + p) % STAGES) * STAGE_BYTES, sbase + SM_S + p * 16384, 16384, bar_peer + 8 * p, rank ^ 1);
                }
              }
              __syncwarp();
              mbar_wait(bar_go + 8, st_ph); st_ph ^= 1;
              if (lane < 4) mbar_arrive(bar_full + 8 * ((s0 + lane) % STAGES));
              skip(); skip(); skip(); skip();
              go_ph ^= 1;
            }
            uint64_t ord = ord0;
            unsigned peek = t8 - 1;
            #pragma unroll 1
            for (int p = 0; p < (pair ? 4 : 2); p++) {
              if (p == 0 || (p == 1 && !pair)) {
                if ((int)(peek - t8) < 0) flag_wait_fast(dep + p * CNT_STRIDE, t8);
                fence_async_global();
              }
              if (p == 2) ord = ord0;
              #pragma unroll 1
              for (int k = 0; k < 6; k++) {
                if (k == 4 && !pair) peek = ld_flag(dep + CNT_STRIDE);
                step(tm, (int)(ord & 15), true); ord >>= 4;
              }
            }
            if (pair) T++;
          } else {
            #pragma unroll 1
            for (int k = 0; k < 16; k++) {
              if (T == 10 && k == 12) hpeek = ld_flag(cnt_base + (L * 256 + C_H) * CNT_STRIDE);
              step(tm, k, true);
            }
          }
        }
        #pragma unroll 1
        for (int i = 0; i < 16; i++) {
          if ((i & 7) == 0) {
            if ((int)(hpeek - t8) < 0) flag_wait(cnt_base + (L * 256 + C_H + (i >> 3)) * CNT_STRIDE, t8);
            fence_async_global();
          }
          if (i == 7) hpeek = ld_flag(cnt_base + (L * 256 + C_H + 1) * CNT_STRIDE);
          #pragma unroll 1
          for (int k = i < 8 ? 0 : 5; k < (i < 8 ? 5 : 7); k++) step(&P.h, 7 * (i & 7) + k, true);
        }
      }
    } else if (warp == 9) {
      if (lane < 9) asm volatile("prefetch.tensormap [%0];" :: "l"(&P.x0 + lane) : "memory");
      int s = (16 + roff) % STAGES; uint32_t ph = (((16 + roff) / STAGES) & 1) ^ 1;
      bool gate = true;
      auto step = [&](const CUtensorMap* t0, const CUtensorMap* t1, int c0, int c1, int chunk, bool no_a = false) {
        if (gate) { bar_sync(8, 96); gate = false; }
        mbar_wait_spin(bar_emptyB + 8 * s, ph);
        if (elect_one()) {
          const uint32_t sb = sbase + s * STAGE_BYTES + 16384;
          if (no_a) mbar_arrive(bar_full + 8 * s);
          mbar_expect_tx(bar_full + 8 * s, 16384);
          tma_load_2d(sb, t0, c0, chunk * 64, bar_full + 8 * s);
          tma_load_2d(sb + 8192, t1, c1, chunk * 64, bar_full + 8 * s);
        }
        if (++s == STAGES) { s = 0; ph ^= 1; }
      };
      #pragma unroll 1
      for (int L = 0; L < 2; L++) {
        #pragma unroll 1
        for (int T = L == 0; T < 11; T++) {
          const bool pair = is_pair(L, T);
          const uint64_t ord0 = (pair || T == 3) ? ord_fresh : 0xFEDCBA9876543210ull;
          #pragma unroll 1
          for (int seg = 0; seg < (pair ? 4 : 1); seg++) {
            const CUtensorMap *t0, *t1; int c0, c1;
            b_tile(P, T + (seg & 1), nj, t0, t1, c0, c1);
            const int k0 = seg < 2 ? 0 : seg * 2 - 2;
            const int k1 = (pair && seg < 2) ? 2 + seg * 2 : 16;
            uint64_t ord = ord0 >> (4 * k0);
            #pragma unroll 1
            for (int k = k0; k < k1; k++) { step(t0, t1, c0, c1, (int)(ord & 15), seg == 2 && k < 4); ord >>= 4; }
          }
          if (pair) T++;
        }
        #pragma unroll 1
        for (int i = 0; i < 16; i++) {
          #pragma unroll 1
          for (int k = i < 8 ? 0 : 5; k < (i < 8 ? 5 : 7); k++) step(&P.wd, &P.wd, nj * 128, nj * 128 + 64, 7 * (i & 7) + k);
        }
      }
    } else if (warp == 10) {
      flag_wait(g_cqcnt + nj * CNT_STRIDE, (epoch + 1) * 16);
      flag_wait(cnt_base + C_X0S * CNT_STRIDE, t8);
      if (l0) mbar_arrive(bar_cs + 72);
      #pragma unroll 1
      for (int job = 0; job < 12; job++) {
        if (job == 4 || job > 9) {
          const int sidx = job == 4 ? 1 : job - 8;
          flag_wait(cnt_base + (sidx == 2 ? C_X2 : (sidx >> 1) * 256 + C_X1) * CNT_STRIDE, t8);
          #pragma unroll 1
          for (int rr = 0; rr < 4; rr++) {
            float2 pv[8];
            #pragma unroll
            for (int j = 0; j < 8; j++) pv[j] = __ldcg(&g_stats[sidx][mi][j][rr * 32 + lane]);
            float ma = 0, qa = 0;
            #pragma unroll
            for (int j = 0; j < 8; j++) ma += pv[j].x;
            ma *= (1.f / 1024.f);
            #pragma unroll
            for (int j = 0; j < 8; j++) { const float e = pv[j].x * (1.f / 128.f) - ma; qa += fmaf(e * e, 128.f, pv[j].y); }
            sts64(sbase + SM_RS + (sidx & 1) * 1024 + rr * 256 + lane * 8, ma, rsqrtf(qa * (1.f / 1024.f) + 1e-5f));
          }
          #pragma unroll
          for (int i = 0; i < 4; i++) mbar_arrive((sidx & 1) ? bar_rsB : bar_rsA);
        } else {
          const int tl = job < 4 ? job : job - 1;
          flag_wait(g_cgcnt + tl * CNT_STRIDE, (epoch + 1) * 32);
          const float4 v = __ldcg((const float4*)&g_csg[nj][tl][0] + lane);
          const uint32_t cso = sbase + SM_CS + (1 + tl) * 576 + ((lane & 1) * 2) * 144 + (lane >> 1) * 8;
          sts64(cso, v.x, v.y); sts64(cso + 144, v.z, v.w);
          __syncwarp();
          if (l0) mbar_arrive(bar_cs + 8 * tl);
        }
      }
      mbar_wait(bar_done, 0);
    } else {
      int ev0 = 0, ev1 = 0;
      uint32_t peer_ph = 0;
      auto wait_sig = [&](int w_) { const int e = w_ ? ev1 : ev0; mbar_wait(bar_sig + (w_ * 2 + (e & 1)) * 8, (e >> 1) & 1); };
      auto set_free = [&](int w_) { const int e = w_ ? ev1 : ev0; if (l0) mbar_arrive(bar_free + (w_ * 2 + (e & 1)) * 8); ev0 += 1 - w_; ev1 += w_; };
      auto own_ready = [&](int it) { if (l0) mbar_arrive(bar_full + 8 * (it % STAGES)); };
      auto store_panel = [&](const CUtensorMap* tm, uint32_t src, int col) {
        if (l0) { tma_store_2d(tm, src, col, row0); tma_store_2d(tm, src + 8192, col, row0 + 64); bulk_commit(); }
      };
      auto drain = [&]() { if (l0) bulk_wait<0>(); };
      auto publish = [&](unsigned* f) { if (l0) { fence_gpu(); flag_add(f); } __syncwarp(); };
      wait_sig(1);
      set_free(1);
      publish(cnt_base + C_X0S * CNT_STRIDE);
      if (l0) flag_add(g_cqcnt + nj * CNT_STRIDE);
      for (int L = 0; L < 2; L++) {
        unsigned* cnt = cnt_base + L * 256 * CNT_STRIDE;
        for (int T = 0; T < NT; T++) {
          const int w_ = T & 1;
          const int itn = roff + L * KS_LAYER + (T == 11 ? KS_LAYER : (T + 1) * 16);
          __syncwarp();
          wait_sig(w_);
          if (T < 2) {
            set_free(w_);
            if (T == 1) publish(g_kvcnt + (L * 8 + nj) * CNT_STRIDE);
          } else if (T == 2) {
            store_panel(&P.h, sbase + SM_S, nj * 128);
            if (l0) mbar_arrive(bar_go);
            drain(); set_free(0);
            publish(cnt + C_O * CNT_STRIDE);
          } else if (T == 3 || T == 11) {
            const bool last = L == 1 && T == 11;
            const CUtensorMap* tm = last ? &P.out : &P.x;
            #pragma unroll 1
            for (int h = 0; h < 2; h++) {
              if (h) { wait_sig(1); }
              if (l0) {
                tma_store_2d(tm, sbase + SM_S + h * 8192, nj * 128, row0 + h * 64);
                tma_store_2d(tm, sbase + SM_S + 16384 + h * 8192, nj * 128 + 64, row0 + h * 64);
                bulk_commit();
              }
              set_free(1);
              __syncwarp();
            }
            if (last) drain();
            else {
              unsigned* c = cnt + (T == 3 ? C_X1 : C_X2) * CNT_STRIDE;
              if (l0) mbar_arrive(bar_go);
              wait_sig(1);
              drain();
              publish(c);
              set_free(1);
              __syncwarp();
              mbar_wait(bar_peer, peer_ph);
              mbar_wait(bar_emptyB + 8 * ((itn + 1) % STAGES), ((itn + 1) / STAGES) & 1);
              own_ready(itn + 4);
              mbar_wait(bar_peer + 8, peer_ph); peer_ph ^= 1;
              own_ready(itn + 5);
            }
          } else {
            store_panel(&P.h, sbase + SM_S + w_ * 16384, nj * 448 + (T - 4) * 64);
            drain(); set_free(w_);
            if (T == 8 || T == 10) publish(cnt + (C_H + (T == 10)) * CNT_STRIDE);
          }
        }
      }
      if (rank == 0 && l0) {
        if (claimed) g_claim[role] = 0;
        if (role == 0) g_claim[88] = epoch + 1;
      }
    }
    __syncwarp();
    cluster_sync_relaxed();
  } else {
    asm volatile("setmaxnreg.inc.sync.aligned.u32 224;");
    const int wg = warp >> 2, w = warp & 3, tid = threadIdx.x & 127;
    const int g = lane >> 2, t = lane & 3;
    const bool elect = tid == 0;
    float acc0[64], acc1[64];
    const int st_row = w * 16 + (lane & 7) + ((lane >> 3) & 1) * 8;
    const int st_ch = lane >> 4;
    const uint32_t myS = sbase + SM_S + wg * 16384;
    const uint32_t zero_v = lane & (gridDim.y - 1);
    uint32_t rel_base;
    asm volatile("mapa.shared::cluster.u32 %0, %1, %2;" : "=r"(rel_base) : "r"(tid == 2 ? bar_emptyB : bar_empty), "r"(tid == 2 ? rank : (uint32_t)(tid & 1)));
    auto release = [&](int slot) { if (tid < 3) asm volatile("mbarrier.arrive.shared::cluster.b64 _, [%0];" :: "r"(rel_base + 8 * slot) : "memory"); };
    int ev = 0;
    auto signal = [&]() { fence_async_smem(); mbar_arrive(bar_sig + (wg * 2 + (ev & 1)) * 8); ev++; };
    auto wait_free = [&]() {
      if (ev >= 2) mbar_wait_c(bar_free + (wg * 2 + (ev & 1)) * 8, ((ev - 2) >> 1) & 1);
      if (ev >= 1) mbar_wait_c(bar_free + (wg * 2 + ((ev - 1) & 1)) * 8, ((ev - 1) >> 1) & 1);
    };
    auto stat_acc = [&](float (&sm)[4], float (&qa)[4], float (&qb)[4], uint32_t a0, uint32_t a1, uint32_t a2, uint32_t a3) {
      mma_bf16_v(sm, a0, a1, a2, a3, 0x3f803f80u, 0x3f803f80u);
      mma_bf16_v(qa, a0, a1, a2, a3, a0, a2);
      mma_bf16_v(qb, a0, a1, a2, a3, a1, a3);
    };
    auto stat_store = [&](float2* dst, const float (&sm)[4], const float (&qa)[4], const float (&qb)[4]) {
      if (t == (g >> 1)) {
        const float q0 = (g & 1) ? qa[1] : qa[0], q1 = (g & 1) ? qb[3] : qb[2];
        dst[0] = make_float2(sm[0], fmaxf(q0 - sm[0] * sm[0] * (1.f / 128.f), 0.f));
        dst[8] = make_float2(sm[2], fmaxf(q1 - sm[2] * sm[2] * (1.f / 128.f), 0.f));
      }
    };
    #pragma unroll
    for (int i = 0; i < 4; i++) asm volatile("st.shared.u32 [%0], %1;" :: "r"(sbase + SM_ONES + (i * 128 + tid) * 4), "r"(0x3f803f80u) : "memory");
    #pragma unroll
    for (int i = 0; i < 64; i++) { acc0[i] = 0.f; acc1[i] = 0.f; }
    pin_regs(acc0); pin_regs(acc1);
    if (wg == 0) {
      int s = 0, n = 16; uint32_t ph = 0;
      #pragma unroll 1
      for (int k = 0; k < n; k++) {
        if (k == STAGES) {
          uint32_t rw;
          mbar_wait_c(bar_role, 0);
          asm volatile("ld.shared.u32 %0, [%1];" : "=r"(rw) : "r"(sm_role) : "memory");
          rw = __reduce_max_sync(~0u, rw);
          if (rw >> 8) {
            if ((rw & 255) >= 64) break;
            n = 16 + STAGES;
          }
        }
        mbar_wait_c(bar_full + 8 * s, ph);
        if (k == n - 1) bar_arrive(2, 256);
        const uint64_t da = desc64((s << 11) + ((SM_BASE >> 4) | 0x10000u)), db = desc64((s << 11) + (((SM_BASE + 16384) >> 4) | 0x2000000u));
        wgmma_fence();
        #pragma unroll
        for (int kk = 0; kk < 4; kk++) {
          const int sd = kk || k != n - 16;
          wgmma_n128(acc0, da + kk * 2, db + kk * 128, sd); wgmma_n128(acc1, da + 512 + kk * 2, db + kk * 128, sd);
        }
        wgmma_commit();
        wgmma_wait<1>();
        if (k > 0) release(s == 0 ? STAGES - 1 : s - 1);
        if (++s == STAGES) { s = 0; ph ^= 1; }
      }
      wgmma_wait<0>();
      release(s == 0 ? STAGES - 1 : s - 1);
    }
    pin_regs(acc0); pin_regs(acc1);
    GET_ROLE(mbar_wait_c)
    uint32_t res_ph = 0;
    if (roff) { mbar_wait_c(bar_res, 0); res_ph = 1; bar_sync(6, 256); }
    if (role >= 64) {
      helper_cta((role - 64) * 2 + rank, epoch, sbase, bar_full, bar_empty);
    } else {
    if (wg == 1) {
      if (roff && elect) startup_loads(P, sbase, bar_res, mi, nj);
      fence_async_smem();
      bar_sync(3 + wg, 128);
      mbar_wait_c(bar_res, res_ph); res_ph ^= 1;
      wgmma_fence();
      #pragma unroll
      for (int kk = 0; kk < 4; kk++) wgmma_n128(acc0, make_desc(SM_BASE + SM_ONES, 16, 0), make_desc(SM_BASE + SM_KV + kk * 2048, 8192, 1024), 1);
      wgmma_commit();
      {
        const uint32_t xrow = sbase + SM_S + tid * 128;
        float piv; { uint32_t u; asm volatile("ld.shared.u32 %0, [%1];" : "=r"(u) : "r"(xrow) : "memory"); piv = bf_lo(u); }
        float s0 = 0, s1 = 0, q0 = 0, q1 = 0;
        #pragma unroll 1
        for (int hp = 0; hp < 2; hp++) {
          uint4 x[8];
          #pragma unroll
          for (int i = 0; i < 8; i++) x[i] = lds128u(xrow + hp * 16384 + (((i ^ lane) & 7) << 4));
          #pragma unroll
          for (int i = 0; i < 8; i++) {
            const uint32_t u[4] = {x[i].x, x[i].y, x[i].z, x[i].w};
            #pragma unroll
            for (int e = 0; e < 4; e++) { float d = bf_lo(u[e]) - piv; s0 += d; q0 = fmaf(d, d, q0); d = bf_hi(u[e]) - piv; s1 += d; q1 = fmaf(d, d, q1); }
          }
        }
        s0 += s1;
        g_stats[0][mi][nj][tid] = make_float2(fmaf(piv, 128.f, s0), fmaxf(q0 + q1 - s0 * s0 * (1.f / 128.f), 0.f));
      }
      wgmma_wait<0>();
      pin_regs(acc0);
      if (tid < 4) {
        float* dst = g_csq[epoch & 1][nj] + t * 32;
        #pragma unroll
        for (int i = 0; i < 8; i++) red_add_v4(dst + i * 4, acc0[i * 8], acc0[i * 8 + 1], acc0[i * 8 + 4], acc0[i * 8 + 5]);
      }
      signal();
    }

    auto combine_stats = [&](int sidx) {
      float2 pv[8];
      #pragma unroll
      for (int j = 0; j < 8; j++) pv[j] = __ldcg(&g_stats[sidx][mi][j][tid]);
      float mean = 0, m2 = 0, q = 0;
      #pragma unroll
      for (int j = 0; j < 8; j++) { mean += pv[j].x; m2 += pv[j].y; }
      mean *= (1.f / 1024.f);
      #pragma unroll
      for (int j = 0; j < 8; j++) { float e = pv[j].x * (1.f / 128.f) - mean; q = fmaf(e, e, q); }
      const float var = (m2 + 128.f * q) * (1.f / 1024.f);
      sts64(sbase + SM_RS + (sidx & 1) * 1024 + tid * 8, mean, rsqrtf(var + 1e-5f));
      mbar_arrive((sidx & 1) ? bar_rsB : bar_rsA);
    };

    if (wg == 1) {
      #pragma unroll
      for (int i = 0; i < 64; i++) { acc0[i] = 0.f; acc1[i] = 0.f; }
    }
    #pragma unroll 1
    for (int item = 0; item < 12; item++) {
      {
        const int item_u = __reduce_max_sync(~0u, item);
        const int L = item_u >= 6;
        const int T = (item_u - 6 * L) * 2 + wg;
        const bool resid = (T == 3 || T == 11);
        const int nk = T == 11 ? 56 : 16;
        if (resid) {
          if (T == 3) {
            const float* src = g_kv[epoch & 1][L][nj];
            const unsigned* kf = g_kvcnt + (L * 8 + nj) * CNT_STRIDE;
            if (w == 0) { while ((int)(ld_flag(kf) - (epoch + 1) * 16) < 0) {} fence_acquire(); }
            bar_sync(4, 128);
            float4 v[8];
            #pragma unroll
            for (int i = 0; i < 8; i++) v[i] = __ldcg((const float4*)src + (w * 8 + i) * 32 + lane);
            const float z = __ldcg(src + 4096 + tid);
            const uint32_t dst = sbase + SM_KV + w * 2560 + g * 80 + t * 4;
            #pragma unroll
            for (int i = 0; i < 8; i++) {
              const uint32_t a = dst + (i >> 2) * 1280 + (i & 3) * 16;
              asm volatile("st.shared.u32 [%0], %1;" :: "r"(a), "r"(pack_bf16(v[i].x, v[i].y)) : "memory");
              asm volatile("st.shared.u32 [%0], %1;" :: "r"(a + 640), "r"(pack_bf16(v[i].z, v[i].w)) : "memory");
            }
            asm volatile("st.shared.v4.u32 [%0], {%1, %1, %1, %1};" :: "r"(sbase + SM_KV + tid * 80 + 64), "r"(pack_bf16(z, z)) : "memory");
            bar_arrive(5, 256);
          }
          uint32_t rs0, rs1;
          if (T == 3) {
            const int itw = roff + L * KS_LAYER + 48;
            rs0 = sbase + (itw % STAGES) * STAGE_BYTES; rs1 = sbase + ((itw + 1) % STAGES) * STAGE_BYTES;
            mbar_wait_c(bar_sig + 8, (L * 3) & 1);
          } else {
            rs0 = sbase + SM_S; rs1 = myS;
            if (elect) {
              wait_free(); fence_async_global();
              mbar_expect_tx(bar_res, 16384);
              tma_load_2d(myS, &P.x, nj * 128 + 64, row0, bar_res);
              tma_load_2d(myS + 8192, &P.x, nj * 128 + 64, row0 + 64, bar_res);
            }
            __syncwarp();
          }
          mbar_wait_c(bar_res2, T == 11);
          #pragma unroll
          for (int p = 0; p < 2; p++) {
            if (p == 1 && T == 11) { mbar_wait_c(bar_res, res_ph); res_ph ^= 1; }
            #pragma unroll
            for (int i = 0; i < 4; i++) {
              const uint32_t ad = (p ? rs1 : rs0) + st_row * 128 + (((i * 2 + st_ch) ^ (st_row & 7)) << 4);
              uint32_t r0[4], r1[4];
              ldmatrix_x4(ad, r0); ldmatrix_x4(ad + 8192, r1);
              #pragma unroll
              for (int e = 0; e < 4; e++) {
                acc0[p * 32 + i * 8 + e * 2] = bf_lo(r0[e]); acc0[p * 32 + i * 8 + e * 2 + 1] = bf_hi(r0[e]);
                acc1[p * 32 + i * 8 + e * 2] = bf_lo(r1[e]); acc1[p * 32 + i * 8 + e * 2 + 1] = bf_hi(r1[e]);
              }
            }
            if (p == 0 && T == 11) bar_arrive(5, 256);
          }
          fence_async_smem();
          if (T == 3) wait_free();
        }
        pin_regs(acc0); pin_regs(acc1);
        int s, prev; uint32_t ph;
        const bool pairX = is_pair(L, T), pairY = T > 0 && is_pair(L, T - 1);
        #pragma unroll 1
        for (int seg = 0; seg < ((L | T) == 0 ? 0 : (pairX || pairY) ? 2 : 1); seg++) {
          int it0 = roff + L * KS_LAYER + T * 16, nks = resid ? nk - TAIL : nk;
          constexpr uint32_t OWN = 2 * STAGES | ((2 * STAGES + 1) << 4);
          uint32_t atab = T == 3 ? 0xFF00u | OWN : 0xFFFFu;
          if (pairX) { if (seg == 0) { nks = 2; atab = 0xFF00u | OWN; } else { it0 += 6; nks = 14; } }
          if (pairY) {
            if (seg == 0) { it0 -= 14; nks = 4; atab = OWN | (((it0 + 4) % STAGES) << 9) | (((it0 + 5) % STAGES) << 13); }
            else { it0 += 4; nks = 12; }
          }
          const uint32_t packed = __reduce_max_sync(~0u, atab | ((it0 % STAGES) << 16) | (((it0 / STAGES) & 1) << 19) | (nks << 20) | zero_v);
          s = (packed >> 16) & 7; ph = (packed >> 19) & 1;
          atab = packed & 0xFFFFu; nks = packed >> 20;
          bar_sync(1 + wg, 256);
          prev = -1;
          mbar_wait_c(bar_full + 8 * s, ph);
          auto kstep = [&](uint32_t aidx) {
            const uint64_t da = desc64((aidx << 10) + ((SM_BASE >> 4) | 0x10000u)), db = desc64((s << 11) + (((SM_BASE + 16384) >> 4) | 0x2000000u));
            wgmma_fence();
            wgmma_n128(acc0, da, db, 1);
            wgmma_n128(acc1, da + 512, db, 1);
            wgmma_n128(acc0, da + 2, db + 128, 1);
            wgmma_n128(acc1, da + 514, db + 128, 1);
            const int cur = s;
            if (++s == STAGES) { s = 0; ph ^= 1; }
            const bool ready = mbar_test_wait(bar_full + 8 * s, ph);
            wgmma_n128(acc0, da + 4, db + 256, 1);
            wgmma_n128(acc1, da + 516, db + 256, 1);
            wgmma_n128(acc0, da + 6, db + 384, 1);
            wgmma_n128(acc1, da + 518, db + 384, 1);
            wgmma_commit();
            wgmma_wait<1>();
            if (prev >= 0) release(prev);
            prev = cur;
            return ready;
          };
          #pragma unroll 1
          while (atab != 0xFFFFu) {
            if (nks == 1) bar_arrive(2 - wg, 256);
            kstep((atab & 15) == 15 ? 2 * s : (atab & 15));
            atab = (atab >> 4) | 0xF000u;
            if (--nks) mbar_wait_c(bar_full + 8 * s, ph);
          }
          if (nks) {
            #pragma unroll 1
            for (;;) {
              const bool ready = kstep(2 * s);
              if (--nks == 0) break;
              if (!ready) mbar_wait_c(bar_full + 8 * s, ph);
              if (nks == 1 && !resid) bar_arrive(2 - wg, 256);
            }
          }
          if (resid) break;
          wgmma_wait<0>();
          pin_regs(acc0); pin_regs(acc1);
          release(prev);
        }

        if (resid) {
          uint32_t pk0[32];
          {
            int sj = s; uint32_t pj = ph;
            #pragma unroll
            for (int j = 0; j < TAIL; j++) {
              mbar_wait_c(bar_full + 8 * sj, pj);
              const uint64_t da = desc64((sj << 11) + ((SM_BASE >> 4) | 0x10000u)), db = desc64((sj << 11) + (((SM_BASE + 16384) >> 4) | 0x2000000u));
              wgmma_fence();
              #pragma unroll
              for (int kk = 0; kk < 4; kk++) wgmma_n128(acc0, da + kk * 2, db + kk * 128, 1);
              wgmma_commit();
              if (j == 0) { wgmma_wait<1>(); release(prev); }
              if (++sj == STAGES) { sj = 0; pj ^= 1; }
            }
            #pragma unroll
            for (int j = 0; j < TAIL; j++) {
              const uint64_t da = desc64((s << 11) + (((SM_BASE + 8192) >> 4) | 0x10000u)), db = desc64((s << 11) + (((SM_BASE + 16384) >> 4) | 0x2000000u));
              wgmma_fence();
              #pragma unroll
              for (int kk = 0; kk < 4; kk++) wgmma_n128(acc1, da + kk * 2, db + kk * 128, 1);
              wgmma_commit();
              wgmma_wait<1>();
              if (j == 0) pin_regs(acc0);
              else release(prev);
              prev = s;
              if (++s == STAGES) s = 0;
              if (j < 2) {
                #pragma unroll
                for (int i = j * 4; i < j * 4 + 4; i++) {
                  uint32_t* pk = pk0 + i * 4;
                  #pragma unroll
                  for (int e = 0; e < 4; e++) pk[e] = pack_bf16(acc0[i * 8 + 2 * e], acc0[i * 8 + 2 * e + 1]);
                  stmatrix_x4(sbase + SM_S + j * 16384 + st_row * 128 + ((((i & 3) * 2 + st_ch) ^ (st_row & 7)) << 4), pk[0], pk[1], pk[2], pk[3]);
                }
                if (j == 1) signal();
              }
            }
            if (!(L == 1 && T == NT - 1)) bar_arrive(2 - wg, 256);
          }
          wgmma_wait<0>();
          pin_regs(acc1);
          release(prev);
          uint32_t pk1[32];
          #pragma unroll
          for (int i = 0; i < 8; i++) {
            #pragma unroll
            for (int e = 0; e < 4; e++) pk1[i * 4 + e] = pack_bf16(acc1[i * 8 + 2 * e], acc1[i * 8 + 2 * e + 1]);
            stmatrix_x4(sbase + SM_S + (i >> 2) * 16384 + 8192 + st_row * 128 + ((((i & 3) * 2 + st_ch) ^ (st_row & 7)) << 4), pk1[i * 4], pk1[i * 4 + 1], pk1[i * 4 + 2], pk1[i * 4 + 3]);
          }
          signal();
          if (!(L == 1 && T == 11)) {
            float sm0[4] = {0, 0, 0, 0}, qa0[4] = {0, 0, 0, 0}, qb0[4] = {0, 0, 0, 0}, sm1[4] = {0, 0, 0, 0}, qa1[4] = {0, 0, 0, 0}, qb1[4] = {0, 0, 0, 0};
            #pragma unroll
            for (int i = 0; i < 8; i++) {
              stat_acc(sm0, qa0, qb0, pk0[i * 4], pk0[i * 4 + 1], pk0[i * 4 + 2], pk0[i * 4 + 3]);
              stat_acc(sm1, qa1, qb1, pk1[i * 4], pk1[i * 4 + 1], pk1[i * 4 + 2], pk1[i * 4 + 3]);
            }
            float2* sd = &g_stats[T == 3 ? L * 2 + 1 : 2][mi][nj][w * 16 + g];
            stat_store(sd, sm0, qa0, qb0); stat_store(sd + 64, sm1, qa1, qb1);
            __syncwarp();
            mbar_arrive(bar_go + 8);
            wait_free();
            signal();
          }
        } else {
          wgmma_wait<0>();
          pin_regs(acc0); pin_regs(acc1);
          if (T == 9 && elect) {
            mbar_wait_c(bar_free, (L * 3 + 2) & 1);
            fence_async_global();
            mbar_expect_tx(bar_res2, 16384);
            tma_load_2d(sbase + SM_S, &P.x, nj * 128, row0, bar_res2);
            tma_load_2d(sbase + SM_S + 8192, &P.x, nj * 128, row0 + 64, bar_res2);
          }
          if (T == 0 && L == 0) {
            mbar_wait_c(bar_cs + 72, 0);
            if (tid < 32) {
              const float4 v = __ldcg((const float4*)&g_csq[epoch & 1][nj][0] + tid);
              sts128(sbase + SM_CS + (tid >> 3) * 144 + (tid & 7) * 16, v.x, v.y, v.z, v.w);
            }
            combine_stats(0);
          }
          mbar_wait_c(T < 3 ? bar_rsA : bar_rsB, L);
          if (T >= 1 && L == 0) mbar_wait_c(bar_cs + 8 * (T < 3 ? T - 1 : T - 2), 0);
          float mu[4], rs[4];
          {
            const uint32_t rb = sbase + SM_RS + (T < 3 ? 0 : 1024) + (w * 16 + g) * 8;
            #pragma unroll
            for (int r = 0; r < 4; r++) { float2 v = lds64(rb + (r & 1) * 64 + (r >> 1) * 512); mu[r] = -v.x; rs[r] = v.y; }
          }
          const uint32_t csb = sbase + SM_CS + (T < 3 ? T : T - 1) * 576 + t * 144;
          auto center = [&](int i1, uint32_t cs) {
            #pragma unroll
            for (int i = 0; i < 8; i++) {
              if (i >= i1) continue;
              float4 c = lds128(cs + i * 16);
              acc0[i * 8 + 0] = fmaf(mu[0], c.x, acc0[i * 8 + 0]); acc0[i * 8 + 1] = fmaf(mu[0], c.y, acc0[i * 8 + 1]);
              acc0[i * 8 + 2] = fmaf(mu[1], c.x, acc0[i * 8 + 2]); acc0[i * 8 + 3] = fmaf(mu[1], c.y, acc0[i * 8 + 3]);
              acc0[i * 8 + 4] = fmaf(mu[0], c.z, acc0[i * 8 + 4]); acc0[i * 8 + 5] = fmaf(mu[0], c.w, acc0[i * 8 + 5]);
              acc0[i * 8 + 6] = fmaf(mu[1], c.z, acc0[i * 8 + 6]); acc0[i * 8 + 7] = fmaf(mu[1], c.w, acc0[i * 8 + 7]);
              acc1[i * 8 + 0] = fmaf(mu[2], c.x, acc1[i * 8 + 0]); acc1[i * 8 + 1] = fmaf(mu[2], c.y, acc1[i * 8 + 1]);
              acc1[i * 8 + 2] = fmaf(mu[3], c.x, acc1[i * 8 + 2]); acc1[i * 8 + 3] = fmaf(mu[3], c.y, acc1[i * 8 + 3]);
              acc1[i * 8 + 4] = fmaf(mu[2], c.z, acc1[i * 8 + 4]); acc1[i * 8 + 5] = fmaf(mu[2], c.w, acc1[i * 8 + 5]);
              acc1[i * 8 + 6] = fmaf(mu[3], c.z, acc1[i * 8 + 6]); acc1[i * 8 + 7] = fmaf(mu[3], c.w, acc1[i * 8 + 7]);
            }
          };
          if (T >= 4) {
            float cc[4], kk[4];
            #pragma unroll
            for (int r = 0; r < 4; r++) { cc[r] = -rs[r] * LOG2E; kk[r] = rcpf(rs[r] * rs[r]); }
            uint32_t pk0[16], pk1[16];
            #pragma unroll
            for (int j = 0; j < 4; j++) {
              const float4 cg = lds128(csb + j * 16), cu = lds128(csb + 64 + j * 16);
              #pragma unroll
              for (int e = 0; e < 4; e++) {
                const int i = j * 4 + e, r = e & 1;
                const float g0 = (e & 2) ? cg.z : cg.x, g1 = (e & 2) ? cg.w : cg.y, u0 = (e & 2) ? cu.z : cu.x, u1 = (e & 2) ? cu.w : cu.y;
                if (i) { mu[r] = __uint_as_float(__float_as_uint(mu[r]) | (pk1[i - 1] & zero_v)); mu[2 + r] = __uint_as_float(__float_as_uint(mu[2 + r]) | (pk0[i - 1] & zero_v)); }
                const float a0 = fmaf(mu[r], g0, acc0[2 * i]), a1 = fmaf(mu[r], g1, acc0[2 * i + 1]);
                const float b0 = fmaf(mu[2 + r], g0, acc1[2 * i]), b1 = fmaf(mu[2 + r], g1, acc1[2 * i + 1]);
                const float h0 = a0 * fmaf(mu[r], u0, acc0[32 + 2 * i]) * rcpf(fmaf(ex2f(a0 * cc[r]), kk[r], kk[r]));
                const float h1 = a1 * fmaf(mu[r], u1, acc0[33 + 2 * i]) * rcpf(fmaf(ex2f(a1 * cc[r]), kk[r], kk[r]));
                const float h2 = b0 * fmaf(mu[2 + r], u0, acc1[32 + 2 * i]) * rcpf(fmaf(ex2f(b0 * cc[2 + r]), kk[2 + r], kk[2 + r]));
                const float h3 = b1 * fmaf(mu[2 + r], u1, acc1[33 + 2 * i]) * rcpf(fmaf(ex2f(b1 * cc[2 + r]), kk[2 + r], kk[2 + r]));
                pk0[i] = pack_bf16(h0, h1); pk1[i] = pack_bf16(h2, h3);
              }
            }
            wait_free();
            if (T == 10) bar_sync(5, 256);
            const uint32_t pb = myS + st_row * 128;
            #pragma unroll
            for (int i = 0; i < 4; i++) {
              const uint32_t off = ((i * 2 + st_ch) ^ (st_row & 7)) << 4;
              stmatrix_x4(pb + off, pk0[i * 4], pk0[i * 4 + 1], pk0[i * 4 + 2], pk0[i * 4 + 3]);
              stmatrix_x4(pb + 8192 + off, pk1[i * 4], pk1[i * 4 + 1], pk1[i * 4 + 2], pk1[i * 4 + 3]);
            }
            signal();
          } else if (T < 2) {
            center(8, csb);
            uint32_t pk0[16], pv0[16], pk1[16], pv1[16];
            #pragma unroll
            for (int i = 0; i < 16; i++) {
              const float ra = rs[i & 1], rb = rs[2 + (i & 1)];
              pk0[i] = pack_bf16(phi(acc0[2 * i], ra, ra * LOG2E), phi(acc0[2 * i + 1], ra, ra * LOG2E));
              pk1[i] = pack_bf16(phi(acc1[2 * i], rb, rb * LOG2E), phi(acc1[2 * i + 1], rb, rb * LOG2E));
              pv0[i] = pack_bf16(acc0[32 + 2 * i] * ra, acc0[33 + 2 * i] * ra);
              pv1[i] = pack_bf16(acc1[32 + 2 * i] * rb, acc1[33 + 2 * i] * rb);
            }
            wait_free();
            if (T == 1) mbar_wait_c(bar_free, (L * 3) & 1);
            {
              const uint32_t pb = sbase + SM_S + st_row * 128;
              #pragma unroll
              for (int i = 0; i < 4; i++) {
                const uint32_t off = ((i * 2 + st_ch) ^ (st_row & 7)) << 4;
                stmatrix_x4(pb + off, pk0[i * 4], pk0[i * 4 + 1], pk0[i * 4 + 2], pk0[i * 4 + 3]);
                stmatrix_x4(pb + 8192 + off, pk1[i * 4], pk1[i * 4 + 1], pk1[i * 4 + 2], pk1[i * 4 + 3]);
                stmatrix_x4(pb + 16384 + off, pv0[i * 4], pv0[i * 4 + 1], pv0[i * 4 + 2], pv0[i * 4 + 3]);
                stmatrix_x4(pb + 24576 + off, pv1[i * 4], pv1[i * 4 + 1], pv1[i * 4 + 2], pv1[i * 4 + 3]);
              }
            }
            float kvd[36];
            #pragma unroll
            for (int i = 0; i < 36; i++) kvd[i] = 0.f;
            pin_regs(kvd);
            fence_async_smem();
            bar_sync(3 + wg, 128);
            wgmma_fence();
            #pragma unroll
            for (int kk = 0; kk < 8; kk++) {
              const uint32_t va = SM_BASE + SM_S + 16384 + kk * 2048;
              wgmma_n72_tt(kvd, make_desc(SM_BASE + SM_S + kk * 2048, 16, 1024), make_desc(va, SM_BASE + SM_ONES - va, 1024), 1);
            }
            wgmma_commit();
            wgmma_wait<0>();
            pin_regs(kvd);
            float* kvg = g_kv[epoch & 1][L][nj];
            #pragma unroll
            for (int b = 0; b < 4; b++) {
              red_add_v4(kvg + T * 2048 + (w * 128 + b * 32 + lane) * 4, w < 2 ? kvd[b * 4] : kvd[16 + b * 4], w < 2 ? kvd[b * 4 + 1] : kvd[17 + b * 4],
                         w < 2 ? kvd[b * 4 + 2] : kvd[18 + b * 4], w < 2 ? kvd[b * 4 + 3] : kvd[19 + b * 4]);
            }
            if (t == 0) { red_add(kvg + 4096 + T * 64 + w * 16 + g, kvd[32]); red_add(kvg + 4096 + T * 64 + w * 16 + g + 8, kvd[34]); }
            signal();
          } else {
            #pragma unroll 1
            for (int p = 0; p < 2; p++) {
              center(4, csb + p * 64);
              uint32_t pqa[16], pqb[16];
              #pragma unroll
              for (int i = 0; i < 16; i++) {
                const float ra = rs[i & 1], rb = rs[2 + (i & 1)];
                pqa[i] = pack_bf16(phi(acc0[2 * i], ra, ra * LOG2E), phi(acc0[2 * i + 1], ra, ra * LOG2E));
                pqb[i] = pack_bf16(phi(acc1[2 * i], rb, rb * LOG2E), phi(acc1[2 * i + 1], rb, rb * LOG2E));
              }
              if (p == 0) {
                uint32_t dep = 0;
                #pragma unroll
                for (int i = 0; i < 16; i++) dep |= pqa[i] | pqb[i];
                bar_sync(5 + (dep & zero_v), 256);
              }
              const uint32_t pb = sbase + SM_S + p * 16384 + st_row * 128;
              #pragma unroll
              for (int hh = 0; hh < 2; hh++) {
                const uint32_t* pq0 = pqa + hh * 8;
                const uint32_t* pq1 = pqb + hh * 8;
                uint32_t bf[5][4];
                #pragma unroll
                for (int nb = 4; nb >= 0; nb--) ldmatrix_x4_t(sbase + SM_KV + (p * 2 + hh) * 2560 + lane * 80 + nb * 16, bf[nb]);
                float d0[5][4], d1[5][4];
                #pragma unroll
                for (int nb = 4; nb >= 0; nb--) {
                  #pragma unroll
                  for (int e = 0; e < 4; e++) { d0[nb][e] = 0.f; d1[nb][e] = 0.f; }
                  mma_bf16(d0[nb], pq0[0], pq0[1], pq0[2], pq0[3], bf[nb][0], bf[nb][1]);
                  mma_bf16(d1[nb], pq1[0], pq1[1], pq1[2], pq1[3], bf[nb][0], bf[nb][1]);
                }
                #pragma unroll
                for (int nb = 4; nb >= 0; nb--) {
                  mma_bf16(d0[nb], pq0[4], pq0[5], pq0[6], pq0[7], bf[nb][2], bf[nb][3]);
                  mma_bf16(d1[nb], pq1[4], pq1[5], pq1[6], pq1[7], bf[nb][2], bf[nb][3]);
                }
                const float i0 = rcpf(d0[4][0] + 1e-6f), i1 = rcpf(d0[4][2] + 1e-6f), i2 = rcpf(d1[4][0] + 1e-6f), i3 = rcpf(d1[4][2] + 1e-6f);
                #pragma unroll
                for (int i = 0; i < 2; i++) {
                  const uint32_t off = ((hh * 4 + i * 2 + st_ch) ^ (st_row & 7)) << 4;
                  stmatrix_x4(pb + off, pack_bf16(d0[2 * i][0] * i0, d0[2 * i][1] * i0), pack_bf16(d0[2 * i][2] * i1, d0[2 * i][3] * i1),
                              pack_bf16(d0[2 * i + 1][0] * i0, d0[2 * i + 1][1] * i0), pack_bf16(d0[2 * i + 1][2] * i1, d0[2 * i + 1][3] * i1));
                  stmatrix_x4(pb + 8192 + off, pack_bf16(d1[2 * i][0] * i2, d1[2 * i][1] * i2), pack_bf16(d1[2 * i][2] * i3, d1[2 * i][3] * i3),
                              pack_bf16(d1[2 * i + 1][0] * i2, d1[2 * i + 1][1] * i2), pack_bf16(d1[2 * i + 1][2] * i3, d1[2 * i + 1][3] * i3));
                }
              }
              if (p == 0) signal();
              else {
                fence_async_smem();
                bar_sync(3, 128);
                if (elect) { tma_store_2d(&P.h, sbase + SM_S + 16384, nj * 128 + 64, row0); tma_store_2d(&P.h, sbase + SM_S + 24576, nj * 128 + 64, row0 + 64); bulk_commit(); }
                mbar_arrive(bar_go + 8);
                if (elect) { bulk_wait<0>(); fence_gpu(); flag_add(g_cnt + (mi * 16 + L * 256 + C_O + 1) * CNT_STRIDE); }
              }
              #pragma unroll
              for (int i = 0; i < 32; i++) { acc0[i] = acc0[32 + i]; acc1[i] = acc1[32 + i]; }
            }
          }
        }
        #pragma unroll
        for (int i = 0; i < 64; i++) { acc0[i] = 0.f; acc1[i] = 0.f; if ((i & 15) == 15) { asm volatile("" : "+f"(acc0[i]), "+f"(acc1[i])); if (T >= 4 && T < 11) __nanosleep(30); } }
      }
    }
    }
    if (elect) mbar_arrive(bar_done);
    cluster_sync_relaxed();
  }
}

typedef CUresult (*EncodeFn)(CUtensorMap*, CUtensorMapDataType, cuuint32_t, void*, const cuuint64_t*, const cuuint64_t*, const cuuint32_t*,
                             const cuuint32_t*, CUtensorMapInterleave, CUtensorMapSwizzle, CUtensorMapL2promotion, CUtensorMapFloatOOBfill);

void make_tmap(EncodeFn enc, CUtensorMap* m, const void* ptr, uint64_t rows, uint64_t cols, CUtensorMapL2promotion promo = CU_TENSOR_MAP_L2_PROMOTION_L2_256B) {
  cuuint64_t dims[2] = {cols, rows};
  cuuint64_t strides[1] = {cols * 2};
  cuuint32_t box[2] = {64, 64};
  cuuint32_t es[2] = {1, 1};
  enc(m, CU_TENSOR_MAP_DATA_TYPE_BFLOAT16, 2, const_cast<void*>(ptr), dims, strides, box, es, CU_TENSOR_MAP_INTERLEAVE_NONE,
      CU_TENSOR_MAP_SWIZZLE_128B, promo, CU_TENSOR_MAP_FLOAT_OOB_FILL_NONE);
}

}

extern "C" void kernel_launch(void* const* d_in, const int* in_sizes, int n_in, void* d_out, int out_size) {
  const __nv_bfloat16* x = (const __nv_bfloat16*)d_in[0];
  const __nv_bfloat16* wqkv = (const __nv_bfloat16*)d_in[1];
  const __nv_bfloat16* wo = (const __nv_bfloat16*)d_in[2];
  const __nv_bfloat16* wg = (const __nv_bfloat16*)d_in[4];
  const __nv_bfloat16* wu = (const __nv_bfloat16*)d_in[5];
  const __nv_bfloat16* wd = (const __nv_bfloat16*)d_in[6];

  void* fn = nullptr;
  cudaDriverEntryPointQueryResult qr;
  cudaGetDriverEntryPoint("cuTensorMapEncodeTiled", &fn, cudaEnableDefault, &qr);
  EncodeFn enc = (EncodeFn)fn;
  void *px, *ph;
  cudaGetSymbolAddress(&px, g_x); cudaGetSymbolAddress(&ph, g_h);
  Params P;
  make_tmap(enc, &P.x0, x, SEQ, DM); make_tmap(enc, &P.x, px, SEQ, DM);
  make_tmap(enc, &P.out, d_out, SEQ, DM); make_tmap(enc, &P.h, ph, SEQ, FF);
  make_tmap(enc, &P.wqkv, wqkv, DM, 3 * DM, CU_TENSOR_MAP_L2_PROMOTION_L2_128B); make_tmap(enc, &P.wo, wo, DM, DM);
  make_tmap(enc, &P.wg, wg, DM, FF); make_tmap(enc, &P.wu, wu, DM, FF); make_tmap(enc, &P.wd, wd, FF, DM);
  cudaFuncSetAttribute(mega_kernel, cudaFuncAttributeMaxDynamicSharedMemorySize, SM_TOTAL);

  cudaLaunchConfig_t cfg = {};
  cfg.gridDim = dim3(132); cfg.blockDim = dim3(384); cfg.dynamicSmemBytes = SM_TOTAL;
  cudaLaunchAttribute at[1];
  at[0].id = cudaLaunchAttributeClusterDimension; at[0].val.clusterDim.x = 2; at[0].val.clusterDim.y = 1; at[0].val.clusterDim.z = 1;
  cfg.attrs = at; cfg.numAttrs = 1;
  int nclusters = 0;
  if (cudaOccupancyMaxActiveClusters(&nclusters, mega_kernel, &cfg) != cudaSuccess) { nclusters = 0; (void)cudaGetLastError(); }
  if (nclusters >= 66) {
    mega_kernel<<<132, 384, SM_TOTAL>>>(wqkv, x, P);
  } else {
    mega_kernel<<<4, 384, SM_TOTAL>>>(wqkv, x, P);
    mega_kernel<<<128, 384, SM_TOTAL>>>(wqkv, x, P);
  }
}
```
